```python
import torch

def _softmax(x, axis=-1):
    return torch.softmax(x, dim=axis)
def _gelu(x):
    return torch.nn.functional.gelu(x, approximate="tanh")
def _silu(x):
    return torch.nn.functional.silu(x)
def _sigmoid(x):
    return torch.sigmoid(x)
def _layernorm(x, axis=-1, eps=1e-5):
    m = x.mean(dim=axis, keepdim=True)
    v = x.var(dim=axis, keepdim=True, unbiased=False)
    return (x - m) / torch.sqrt(v + eps)
def _scatter_add(tgt, idx, src, axis=0):
    return tgt.clone().index_add_(axis, idx, src)
def _segment_sum(src, seg, n):
    out = torch.zeros((n,) + src.shape[1:], dtype=src.dtype)
    return out.index_add_(0, seg, src)
def _pad(x, pw):
    flat = tuple(v for pair in reversed(pw) for v in pair)
    return torch.nn.functional.pad(x, flat)

kernel_name = 'interleave_layers__spectral_gfnet__glu_gated_reglu__prompt'

def setup_inputs():

    _w = (lambda a: (lambda t: t.to(torch.bfloat16) if t.is_floating_point() else t)(torch.as_tensor(a)))
    def _A_setup():
        B, S, D = 1, 2048, 512
        Df = D // 2 + 1
        return {
            "x": _w((lambda *s: torch.randn(*s, dtype=torch.bfloat16) * 0.05)(B, S, D)),
            "w_r": _w((lambda *s: torch.randn(*s, dtype=torch.bfloat16) * 0.4)(S, Df) * 0.02),
            "w_i": _w((lambda *s: torch.randn(*s, dtype=torch.bfloat16) * 0.4)(S, Df) * 0.02),
        }
    _A_in = _A_setup()

    def _B_setup():
        B, S, D, F = 1, 2048, 512, 1792
        return {
            "x": _w((lambda *s: torch.randn(*s, dtype=torch.bfloat16) * 0.05)(B, S, D)),
            "W_gate": _w((lambda *s: torch.randn(*s, dtype=torch.bfloat16) * 0.2)(D, F) * (2.0 / D) ** 0.5),
            "W_up": _w((lambda *s: torch.randn(*s, dtype=torch.bfloat16) * 0.2)(D, F) * (2.0 / D) ** 0.5),
            "W_down": _w((lambda *s: torch.randn(*s, dtype=torch.bfloat16) * 0.2)(F, D) * (1.0 / F) ** 0.5),
        }
    _B_in = _B_setup()

    return {
        "A_x": _A_in["x"],
        "A_w_r": _A_in["w_r"],
        "A_w_i": _A_in["w_i"],
        "B_x": _B_in["x"],
        "B_W_gate": _B_in["W_gate"],
        "B_W_up": _B_in["W_up"],
        "B_W_down": _B_in["W_down"],
    }

def reference(A_x, A_w_r, A_w_i, B_x, B_W_gate, B_W_up, B_W_down):
    def _A_ref(x, w_r, w_i):
        B, S, D = x.shape
        X = (lambda x, axes=(-2,-1): torch.fft.rfft2(x.float(), dim=axes))(x, axes=(-2, -1))
        W = w_r + 1j * w_i
        X = X * W
        y = (lambda x, s, axes=(-2,-1): torch.fft.irfft2(x, s=s, dim=axes).to(torch.bfloat16))(X, (S, D), axes=(-2, -1))
        return y

    def _B_ref(x, W_gate, W_up, W_down):
        gate = torch.einsum("bsd,df->bsf", x, W_gate)
        up = torch.einsum("bsd,df->bsf", x, W_up)
        gate = gate * (lambda x, dt: x.to(dt))(gate > 0, gate.dtype)
        h = gate * up
        return torch.einsum("bsf,fd->bsd", h, W_down)

    x = A_x
    x = x + _A_ref(_layernorm(x, axis=-1), A_w_r, A_w_i)
    x = x + _B_ref(_layernorm(x, axis=-1), B_W_gate, B_W_up, B_W_down)
    x = x + _A_ref(_layernorm(x, axis=-1), A_w_r, A_w_i)
    x = x + _B_ref(_layernorm(x, axis=-1), B_W_gate, B_W_up, B_W_down)
    return x
```

```cpp
#include <cuda_runtime.h>
#include <cuda_bf16.h>
#include <cuda.h>
#include <stdint.h>

__device__ __align__(128) const uint32_t g_tab[8448] = {
0x3f803f80,0xbf803f80,0x3f803f80,0xbf803f80,0x3f803f80,0xbf803f80,0x3f803f80,0xbf803f80,0x3f803f80,0xbf803f80,0x3f803f80,0xbf803f80,0x3f803f80,0xbf803f80,0x3f803f80,0xbf803f80,
0x3f7b3f80,0xbe488000,0x3f553f6d,0xbf0ebec4,0x3f0e3f35,0xbf55bf35,0x3e483ec4,0xbf7bbf6d,0xbe480000,0xbf7bbf80,0xbf0ebec4,0xbf55bf6d,0xbf55bf35,0xbf0ebf35,0xbf7bbf6d,0xbe48bec4,
0x3f6d3f80,0xbec48000,0x3ec43f35,0xbf6dbf35,0xbec40000,0xbf6dbf80,0xbf6dbf35,0xbec4bf35,0xbf6dbf80,0x3ec48000,0xbec4bf35,0x3f6d3f35,0x3ec40000,0x3f6d3f80,0x3f6d3f35,0x3ec43f35,
0x3f553f80,0xbf0e8000,0xbe483ec4,0xbf7bbf6d,0xbf7bbf35,0xbe48bf35,0xbf0ebf6d,0x3f553ec4,0x3f0e0000,0x3f553f80,0x3f7b3f6d,0xbe483ec4,0x3e483f35,0xbf7bbf35,0xbf55bec4,0xbf0ebf6d,
0x3f353f80,0xbf358000,0xbf350000,0xbf35bf80,0xbf35bf80,0x3f358000,0x3f350000,0x3f353f80,0x3f353f80,0xbf358000,0xbf350000,0xbf35bf80,0xbf35bf80,0x3f358000,0x3f350000,0x3f353f80,
0x3f0e3f80,0xbf558000,0xbf7bbec4,0xbe48bf6d,0x3e48bf35,0x3f7b3f35,0x3f553f6d,0xbf0e3ec4,0xbf550000,0xbf0ebf80,0xbe48bf6d,0x3f7b3ec4,0x3f7b3f35,0xbe483f35,0xbf0e3ec4,0xbf55bf6d,
0x3ec43f80,0xbf6d8000,0xbf6dbf35,0x3ec4bf35,0x3f6d0000,0x3ec43f80,0xbec43f35,0xbf6dbf35,0xbec4bf80,0x3f6d8000,0x3f6d3f35,0xbec43f35,0xbf6d0000,0xbec4bf80,0x3ec4bf35,0x3f6d3f35,
0x3e483f80,0xbf7b8000,0xbf0ebf6d,0x3f55bec4,0x3f553f35,0xbf0e3f35,0xbf7bbec4,0x3e48bf6d,0x3f7b0000,0x3e483f80,0xbf553ec4,0xbf0ebf6d,0x3f0ebf35,0x3f553f35,0xbe483f6d,0xbf7bbec4,
0x3f803f80,0xbf803f80,0x3f803f80,0xbf803f80,0x3f803f80,0xbf803f80,0x3f803f80,0xbf803f80,0x3f803f80,0xbf803f80,0x3f803f80,0xbf803f80,0x3f803f80,0xbf803f80,0x3f803f80,0xbf803f80,
0xbf7bbf80,0x3e488000,0xbf55bf6d,0x3f0e3ec4,0xbf0ebf35,0x3f553f35,0xbe48bec4,0x3f7b3f6d,0x3e480000,0x3f7b3f80,0x3f0e3ec4,0x3f553f6d,0x3f553f35,0x3f0e3f35,0x3f7b3f6d,0x3e483ec4,
0x3f6d3f80,0xbec48000,0x3ec43f35,0xbf6dbf35,0xbec40000,0xbf6dbf80,0xbf6dbf35,0xbec4bf35,0xbf6dbf80,0x3ec48000,0xbec4bf35,0x3f6d3f35,0x3ec40000,0x3f6d3f80,0x3f6d3f35,0x3ec43f35,
0xbf55bf80,0x3f0e8000,0x3e48bec4,0x3f7b3f6d,0x3f7b3f35,0x3e483f35,0x3f0e3f6d,0xbf55bec4,0xbf0e0000,0xbf55bf80,0xbf7bbf6d,0x3e48bec4,0xbe48bf35,0x3f7b3f35,0x3f553ec4,0x3f0e3f6d,
0x3f353f80,0xbf358000,0xbf350000,0xbf35bf80,0xbf35bf80,0x3f358000,0x3f350000,0x3f353f80,0x3f353f80,0xbf358000,0xbf350000,0xbf35bf80,0xbf35bf80,0x3f358000,0x3f350000,0x3f353f80,
0xbf0ebf80,0x3f558000,0x3f7b3ec4,0x3e483f6d,0xbe483f35,0xbf7bbf35,0xbf55bf6d,0x3f0ebec4,0x3f550000,0x3f0e3f80,0x3e483f6d,0xbf7bbec4,0xbf7bbf35,0x3e48bf35,0x3f0ebec4,0x3f553f6d,
0x3ec43f80,0xbf6d8000,0xbf6dbf35,0x3ec4bf35,0x3f6d0000,0x3ec43f80,0xbec43f35,0xbf6dbf35,0xbec4bf80,0x3f6d8000,0x3f6d3f35,0xbec43f35,0xbf6d0000,0xbec4bf80,0x3ec4bf35,0x3f6d3f35,
0xbe48bf80,0x3f7b8000,0x3f0e3f6d,0xbf553ec4,0xbf55bf35,0x3f0ebf35,0x3f7b3ec4,0xbe483f6d,0xbf7b0000,0xbe48bf80,0x3f55bec4,0x3f0e3f6d,0xbf0e3f35,0xbf55bf35,0x3e48bf6d,0x3f7b3ec4,
0x3f80,0xbf808000,0xbf80,0x3f808000,0x3f80,0xbf808000,0xbf80,0x3f808000,0x3f80,0xbf808000,0xbf80,0x3f808000,0x3f80,0xbf808000,0xbf80,0x3f808000,
0xbe483f80,0xbf7b8000,0x3f0ebf6d,0x3f553ec4,0xbf553f35,0xbf0ebf35,0x3f7bbec4,0x3e483f6d,0xbf7b0000,0x3e48bf80,0x3f553ec4,0xbf0e3f6d,0xbf0ebf35,0x3f55bf35,0x3e483f6d,0xbf7b3ec4,
0xbec43f80,0xbf6d8000,0x3f6dbf35,0x3ec43f35,0xbf6d0000,0x3ec4bf80,0x3ec43f35,0xbf6d3f35,0x3ec4bf80,0x3f6d8000,0xbf6d3f35,0xbec4bf35,0x3f6d0000,0xbec43f80,0xbec4bf35,0x3f6dbf35,
0xbf0e3f80,0xbf558000,0x3f7bbec4,0xbe483f6d,0xbe48bf35,0x3f7bbf35,0xbf553f6d,0xbf0ebec4,0x3f550000,0xbf0e3f80,0x3e48bf6d,0x3f7bbec4,0xbf7b3f35,0xbe48bf35,0x3f0e3ec4,0xbf553f6d,
0xbf353f80,0xbf358000,0x3f350000,0xbf353f80,0x3f35bf80,0x3f358000,0xbf350000,0x3f35bf80,0xbf353f80,0xbf358000,0x3f350000,0xbf353f80,0x3f35bf80,0x3f358000,0xbf350000,0x3f35bf80,
0xbf553f80,0xbf0e8000,0x3e483ec4,0xbf7b3f6d,0x3f7bbf35,0xbe483f35,0x3f0ebf6d,0x3f55bec4,0xbf0e0000,0x3f55bf80,0xbf7b3f6d,0xbe48bec4,0xbe483f35,0xbf7b3f35,0x3f55bec4,0xbf0e3f6d,
0xbf6d3f80,0xbec48000,0xbec43f35,0xbf6d3f35,0x3ec40000,0xbf6d3f80,0x3f6dbf35,0xbec43f35,0x3f6dbf80,0x3ec48000,0x3ec4bf35,0x3f6dbf35,0xbec40000,0x3f6dbf80,0xbf6d3f35,0x3ec4bf35,
0xbf7b3f80,0xbe488000,0xbf553f6d,0xbf0e3ec4,0xbf0e3f35,0xbf553f35,0xbe483ec4,0xbf7b3f6d,0x3e480000,0xbf7b3f80,0x3f0ebec4,0xbf553f6d,0x3f55bf35,0xbf0e3f35,0x3f7bbf6d,0xbe483ec4,
0x3f80,0xbf808000,0xbf80,0x3f808000,0x3f80,0xbf808000,0xbf80,0x3f808000,0x3f80,0xbf808000,0xbf80,0x3f808000,0x3f80,0xbf808000,0xbf80,0x3f808000,
0x3e48bf80,0x3f7b8000,0xbf0e3f6d,0xbf55bec4,0x3f55bf35,0x3f0e3f35,0xbf7b3ec4,0xbe48bf6d,0x3f7b0000,0xbe483f80,0xbf55bec4,0x3f0ebf6d,0x3f0e3f35,0xbf553f35,0xbe48bf6d,0x3f7bbec4,
0xbec43f80,0xbf6d8000,0x3f6dbf35,0x3ec43f35,0xbf6d0000,0x3ec4bf80,0x3ec43f35,0xbf6d3f35,0x3ec4bf80,0x3f6d8000,0xbf6d3f35,0xbec4bf35,0x3f6d0000,0xbec43f80,0xbec4bf35,0x3f6dbf35,
0x3f0ebf80,0x3f558000,0xbf7b3ec4,0x3e48bf6d,0x3e483f35,0xbf7b3f35,0x3f55bf6d,0x3f0e3ec4,0xbf550000,0x3f0ebf80,0xbe483f6d,0xbf7b3ec4,0x3f7bbf35,0x3e483f35,0xbf0ebec4,0x3f55bf6d,
0xbf353f80,0xbf358000,0x3f350000,0xbf353f80,0x3f35bf80,0x3f358000,0xbf350000,0x3f35bf80,0xbf353f80,0xbf358000,0x3f350000,0xbf353f80,0x3f35bf80,0x3f358000,0xbf350000,0x3f35bf80,
0x3f55bf80,0x3f0e8000,0xbe48bec4,0x3f7bbf6d,0xbf7b3f35,0x3e48bf35,0xbf0e3f6d,0xbf553ec4,0x3f0e0000,0xbf553f80,0x3f7bbf6d,0x3e483ec4,0x3e48bf35,0x3f7bbf35,0xbf553ec4,0x3f0ebf6d,
0xbf6d3f80,0xbec48000,0xbec43f35,0xbf6d3f35,0x3ec40000,0xbf6d3f80,0x3f6dbf35,0xbec43f35,0x3f6dbf80,0x3ec48000,0x3ec4bf35,0x3f6dbf35,0xbec40000,0x3f6dbf80,0xbf6d3f35,0x3ec4bf35,
0x3f7bbf80,0x3e488000,0x3f55bf6d,0x3f0ebec4,0x3f0ebf35,0x3f55bf35,0x3e48bec4,0x3f7bbf6d,0xbe480000,0x3f7bbf80,0xbf0e3ec4,0x3f55bf6d,0xbf553f35,0x3f0ebf35,0xbf7b3f6d,0x3e48bec4,
0,0x3f800000,0,0x80000000,0,0x3f3504f3,0,0xbf3504f3,0,0,0,0xbf800000,0,0xbf3504f3,0,0xbf3504f3,
0x3f800000,0,0x80000000,0x3f800000,0x3f7fb10f,0x3d48fb30,0xbd48fb30,0x3f7fb10f,0x3f7ec46d,0x3dc8bd36,0xbdc8bd36,0x3f7ec46d,0x3f7d3aac,0x3e164083,0xbe164083,0x3f7d3aac,
0x3f800000,0,0x80000000,0x3f800000,0x3f7ec46d,0x3dc8bd36,0xbdc8bd36,0x3f7ec46d,0x3f7b14be,0x3e47c5c2,0xbe47c5c2,0x3f7b14be,0x3f74fa0b,0x3e94a031,0xbe94a031,0x3f74fa0b,
0x3f800000,0,0x80000000,0x3f800000,0x3f7d3aac,0x3e164083,0xbe164083,0x3f7d3aac,0x3f74fa0b,0x3e94a031,0xbe94a031,0x3f74fa0b,0x3f676bd8,0x3edae880,0xbedae880,0x3f676bd8,
0x3f800000,0,0x80000000,0x3f800000,0x3f7b14be,0x3e47c5c2,0xbe47c5c2,0x3f7b14be,0x3f6c835e,0x3ec3ef15,0xbec3ef15,0x3f6c835e,0x3f54db31,0x3f0e39da,0xbf0e39da,0x3f54db31,
0x3f800000,0,0x80000000,0x3f800000,0x3f7853f8,0x3e78cfcc,0xbe78cfcc,0x3f7853f8,0x3f61c598,0x3ef15aea,0xbef15aea,0x3f61c598,0x3f3daef9,0x3f2beb4a,0xbf2beb4a,0x3f3daef9,
0x3f800000,0,0x80000000,0x3f800000,0x3f74fa0b,0x3e94a031,0xbe94a031,0x3f74fa0b,0x3f54db31,0x3f0e39da,0xbf0e39da,0x3f54db31,0x3f226799,0x3f45e403,0xbf45e403,0x3f226799,
0x3f800000,0,0x80000000,0x3f800000,0x3f710908,0x3eac7cd4,0xbeac7cd4,0x3f710908,0x3f45e403,0x3f226799,0xbf226799,0x3f45e403,0x3f039c3d,0x3f5b941a,0xbf5b941a,0x3f039c3d,
0,0x3f6c835e,0,0xbec3ef15,0,0x3ec3ef15,0,0xbf6c835e,0,0xbec3ef15,0,0xbf6c835e,0,0xbf6c835e,0,0xbec3ef15,
0x3f7fec43,0x3cc90ab0,0xbcc90ab0,0x3f7fec43,0x3f7f4e6d,0x3d96a905,0xbd96a905,0x3f7f4e6d,0x3f7e1324,0x3dfab273,0xbdfab273,0x3f7e1324,0x3f7c3b28,0x3e2f10a2,0xbe2f10a2,0x3f7c3b28,
0x3f7fb10f,0x3d48fb30,0xbd48fb30,0x3f7fb10f,0x3f7d3aac,0x3e164083,0xbe164083,0x3f7d3aac,0x3f7853f8,0x3e78cfcc,0xbe78cfcc,0x3f7853f8,0x3f710908,0x3eac7cd4,0xbeac7cd4,0x3f710908,
0x3f7f4e6d,0x3d96a905,0xbd96a905,0x3f7f4e6d,0x3f79c79d,0x3e605c13,0xbe605c13,0x3f79c79d,0x3f6ed89e,0x3eb8442a,0xbeb8442a,0x3f6ed89e,0x3f5ebe05,0x3efc5d27,0xbefc5d27,0x3f5ebe05,
0x3f7ec46d,0x3dc8bd36,0xbdc8bd36,0x3f7ec46d,0x3f74fa0b,0x3e94a031,0xbe94a031,0x3f74fa0b,0x3f61c598,0x3ef15aea,0xbef15aea,0x3f61c598,0x3f45e403,0x3f226799,0xbf226799,0x3f45e403,
0x3f7e1324,0x3dfab273,0xbdfab273,0x3f7e1324,0x3f6ed89e,0x3eb8442a,0xbeb8442a,0x3f6ed89e,0x3f514d3d,0x3f13682a,0xbf13682a,0x3f514d3d,0x3f273656,0x3f41d870,0xbf41d870,0x3f273656,
0x3f7d3aac,0x3e164083,0xbe164083,0x3f7d3aac,0x3f676bd8,0x3edae880,0xbedae880,0x3f676bd8,0x3f3daef9,0x3f2beb4a,0xbf2beb4a,0x3f3daef9,0x3f039c3d,0x3f5b941a,0xbf5b941a,0x3f039c3d,
0x3f7c3b28,0x3e2f10a2,0xbe2f10a2,0x3f7c3b28,0x3f5ebe05,0x3efc5d27,0xbefc5d27,0x3f5ebe05,0x3f273656,0x3f41d870,0xbf41d870,0x3f273656,0x3eb8442a,0x3f6ed89e,0xbf6ed89e,0x3eb8442a,
0,0x3f7b14be,0,0xbe47c5c2,0,0x3f0e39da,0,0xbf54db31,0,0xbe47c5c2,0,0xbf7b14be,0,0xbf54db31,0,0xbf0e39da,
0x3f7ffb11,0x3c490e90,0xbc490e90,0x3f7ffb11,0x3f7f84ab,0x3d7b2b74,0xbd7b2b74,0x3f7f84ab,0x3f7e70b0,0x3de1bc2e,0xbde1bc2e,0x3f7e70b0,0x3f7cbfc9,0x3e22abb6,0xbe22abb6,0x3f7cbfc9,
0x3f7fec43,0x3cc90ab0,0xbcc90ab0,0x3f7fec43,0x3f7e1324,0x3dfab273,0xbdfab273,0x3f7e1324,0x3f79c79d,0x3e605c13,0xbe605c13,0x3f79c79d,0x3f731447,0x3ea09ae5,0xbea09ae5,0x3f731447,
0x3f7fd397,0x3d16c32c,0xbd16c32c,0x3f7fd397,0x3f7baccd,0x3e3b6ecf,0xbe3b6ecf,0x3f7baccd,0x3f721352,0x3ea68f12,0xbea68f12,0x3f721352,0x3f633c5a,0x3eebcbbb,0xbeebcbbb,0x3f633c5a,
0x3f7fb10f,0x3d48fb30,0xbd48fb30,0x3f7fb10f,0x3f7853f8,0x3e78cfcc,0xbe78cfcc,0x3f7853f8,0x3f676bd8,0x3edae880,0xbedae880,0x3f676bd8,0x3f4d9f02,0x3f187fc0,0xbf187fc0,0x3f4d9f02,
0x3f7f84ab,0x3d7b2b74,0xbd7b2b74,0x3f7f84ab,0x3f740bdd,0x3e9aa086,0xbe9aa086,0x3f740bdd,0x3f59f26a,0x3f064b82,0xbf064b82,0x3f59f26a,0x3f32c8c9,0x3f373a23,0xbf373a23,0x3f32c8c9,
0x3f7f4e6d,0x3d96a905,0xbd96a905,0x3f7f4e6d,0x3f6ed89e,0x3eb8442a,0xbeb8442a,0x3f6ed89e,0x3f49d112,0x3f1d7fd1,0xbf1d7fd1,0x3f49d112,0x3f13682a,0x3f514d3d,0xbf514d3d,0x3f13682a,
0x3f7f0e58,0x3dafb680,0xbdafb680,0x3f7f0e58,0x3f68bf3c,0x3ed53641,0xbed53641,0x3f68bf3c,0x3f373a23,0x3f32c8c9,0xbf32c8c9,0x3f373a23,0x3ee0924f,0x3f660f88,0xbf660f88,0x3ee0924f,
0,0x3f54db31,0,0xbf0e39da,0,0x3e47c5c2,0,0xbf7b14be,0,0xbf0e39da,0,0xbf54db31,0,0xbf7b14be,0,0xbe47c5c2,
0x3f7fd397,0x3d16c32c,0xbd16c32c,0x3f7fd397,0x3f7f0e58,0x3dafb680,0xbdafb680,0x3f7f0e58,0x3f7dabcc,0x3e09cf86,0xbe09cf86,0x3f7dabcc,0x3f7baccd,0x3e3b6ecf,0xbe3b6ecf,0x3f7baccd,
0x3f7f4e6d,0x3d96a905,0xbd96a905,0x3f7f4e6d,0x3f7c3b28,0x3e2f10a2,0xbe2f10a2,0x3f7c3b28,0x3f76ba07,0x3e888e93,0xbe888e93,0x3f76ba07,0x3f6ed89e,0x3eb8442a,0xbeb8442a,0x3f6ed89e,
0x3f7e70b0,0x3de1bc2e,0xbde1bc2e,0x3f7e70b0,0x3f778bc5,0x3e827dc0,0xbe827dc0,0x3f778bc5,0x3f6b4b0c,0x3ec9b953,0xbec9b953,0x3f6b4b0c,0x3f59f26a,0x3f064b82,0xbf064b82,0x3f59f26a,
0x3f7d3aac,0x3e164083,0xbe164083,0x3f7d3aac,0x3f710908,0x3eac7cd4,0xbeac7cd4,0x3f710908,0x3f5b941a,0x3f039c3d,0xbf039c3d,0x3f5b941a,0x3f3daef9,0x3f2beb4a,0xbf2beb4a,0x3f3daef9,
0x3f7baccd,0x3e3b6ecf,0xbe3b6ecf,0x3f7baccd,0x3f68bf3c,0x3ed53641,0xbed53641,0x3f68bf3c,0x3f47de65,0x3f1ff6cb,0xbf1ff6cb,0x3f47de65,0x3f1b02c6,0x3f4bbbf8,0xbf4bbbf8,0x3f1b02c6,
0x3f79c79d,0x3e605c13,0xbe605c13,0x3f79c79d,0x3f5ebe05,0x3efc5d27,0xbefc5d27,0x3f5ebe05,0x3f3085bb,0x3f396842,0xbf396842,0x3f3085bb,0x3ee63375,0x3f64aa59,0xbf64aa59,0x3ee63375,
0x3f778bc5,0x3e827dc0,0xbe827dc0,0x3f778bc5,0x3f531849,0x3f10d3cd,0xbf10d3cd,0x3f531849,0x3f15f6d9,0x3f4f7a1f,0xbf4f7a1f,0x3f15f6d9,0x3e8e9a22,0x3f75dec6,0xbf75dec6,0x3e8e9a22,
0x3f800000,0,0x3f7b14be,0x3e47c5c2,0x3f6c835e,0x3ec3ef15,0x3f54db31,0x3f0e39da,0x3f3504f3,0x3f3504f3,0x3f0e39da,0x3f54db31,0x3ec3ef15,0x3f6c835e,0x3e47c5c2,0x3f7b14be,
0x3f800000,0,0x3f79c79d,0x3e605c13,0x3f676bd8,0x3edae880,0x3f49d112,0x3f1d7fd1,0x3f226799,0x3f45e403,0x3ee63375,0x3f64aa59,0x3e78cfcc,0x3f7853f8,0x3cc90ab0,0x3f7fec43,
0x3f800000,0,0x3f7853f8,0x3e78cfcc,0x3f61c598,0x3ef15aea,0x3f3daef9,0x3f2beb4a,0x3f0e39da,0x3f54db31,0x3eac7cd4,0x3f710908,0x3dc8bd36,0x3f7ec46d,0xbe164083,0x3f7d3aac,
0x3f800000,0,0x3f76ba07,0x3e888e93,0x3f5b941a,0x3f039c3d,0x3f3085bb,0x3f396842,0x3ef15aea,0x3f61c598,0x3e605c13,0x3f79c79d,0xbd48fb30,0x3f7fb10f,0xbea09ae5,0x3f731447,
0x3f800000,0,0x3f74fa0b,0x3e94a031,0x3f54db31,0x3f0e39da,0x3f226799,0x3f45e403,0x3ec3ef15,0x3f6c835e,0x3dc8bd36,0x3f7ec46d,0xbe47c5c2,0x3f7b14be,0xbef15aea,0x3f61c598,
0x3f800000,0,0x3f731447,0x3ea09ae5,0x3f4d9f02,0x3f187fc0,0x3f13682a,0x3f514d3d,0x3e94a031,0x3f74fa0b,0xbcc90ab0,0x3f7fec43,0xbeac7cd4,0x3f710908,0xbf1d7fd1,0x3f49d112,
0x3f800000,0,0x3f710908,0x3eac7cd4,0x3f45e403,0x3f226799,0x3f039c3d,0x3f5b941a,0x3e47c5c2,0x3f7b14be,0xbe164083,0x3f7d3aac,0xbef15aea,0x3f61c598,0xbf3daef9,0x3f2beb4a,
0x3f800000,0,0x3f6ed89e,0x3eb8442a,0x3f3daef9,0x3f2beb4a,0x3ee63375,0x3f64aa59,0x3dc8bd36,0x3f7ec46d,0xbe888e93,0x3f76ba07,0xbf187fc0,0x3f4d9f02,0xbf584853,0x3f08f59b,
0x3f7ec46d,0x3dc8bd36,0x3f74fa0b,0x3e94a031,0x3f61c598,0x3ef15aea,0x3f45e403,0x3f226799,0x3f226799,0x3f45e403,0x3ef15aea,0x3f61c598,0x3e94a031,0x3f74fa0b,0x3dc8bd36,0x3f7ec46d,
0x3f7e70b0,0x3de1bc2e,0x3f721352,0x3ea68f12,0x3f59f26a,0x3f064b82,0x3f373a23,0x3f32c8c9,0x3f0b9a6b,0x3f5695e5,0x3eb263ef,0x3f6ff573,0x3e09cf86,0x3f7dabcc,0xbdafb680,0x3f7f0e58,
0x3f7e1324,0x3dfab273,0x3f6ed89e,0x3eb8442a,0x3f514d3d,0x3f13682a,0x3f273656,0x3f41d870,0x3ee63375,0x3f64aa59,0x3e605c13,0x3f79c79d,0xbcc90ab0,0x3f7fec43,0xbe888e93,0x3f76ba07,
0x3f7dabcc,0x3e09cf86,0x3f6b4b0c,0x3ec9b953,0x3f47de65,0x3f1ff6cb,0x3f15f6d9,0x3f4f7a1f,0x3eb263ef,0x3f6ff573,0x3dafb680,0x3f7f0e58,0xbe3b6ecf,0x3f7baccd,0xbee0924f,0x3f660f88,
0x3f7d3aac,0x3e164083,0x3f676bd8,0x3edae880,0x3f3daef9,0x3f2beb4a,0x3f039c3d,0x3f5b941a,0x3e78cfcc,0x3f7853f8,0xbd48fb30,0x3f7fb10f,0xbeac7cd4,0x3f710908,0xbf187fc0,0x3f4d9f02,
0x3f7cbfc9,0x3e22abb6,0x3f633c5a,0x3eebcbbb,0x3f32c8c9,0x3f373a23,0x3ee0924f,0x3f660f88,0x3e09cf86,0x3f7dabcc,0xbe3b6ecf,0x3f7baccd,0xbef6e0cb,0x3f604621,0xbf3b8f3b,0x3f2e3bde,
0x3f7c3b28,0x3e2f10a2,0x3f5ebe05,0x3efc5d27,0x3f273656,0x3f41d870,0x3eb8442a,0x3f6ed89e,0x3cc90ab0,0x3f7fec43,0xbea09ae5,0x3f731447,0xbf1d7fd1,0x3f49d112,0xbf584853,0x3f08f59b,
0x3f7baccd,0x3e3b6ecf,0x3f59f26a,0x3f064b82,0x3f1b02c6,0x3f4bbbf8,0x3e8e9a22,0x3f75dec6,0xbdafb680,0x3f7f0e58,0xbee0924f,0x3f660f88,0xbf3b8f3b,0x3f2e3bde,0xbf6db293,0x3ebe1d4a,
0x3f80,0x3f80,0x3f80,0xbf80,0x3f80,0x3f80,0x3f80,0xbf80,0x3f80,0x3f80,0x3f80,0xbf80,0x3f80,0x3f80,0x3f80,0xbf80,
0x3f808000,0x3f808000,0x3f808000,0xbf808000,0x3f808000,0x3f808000,0x3f808000,0xbf808000,0x3f808000,0x3f808000,0x3f808000,0xbf808000,0x3f808000,0x3f808000,0x3f808000,0xbf808000,
0x3f80,0x3f353f35,0x3f80,0xbf35bf35,0x3f800000,0x3f35bf35,0x3f800000,0xbf353f35,0xbf80,0xbf35bf35,0xbf80,0x3f353f35,0xbf800000,0xbf353f35,0xbf800000,0x3f35bf35,
0x3f808000,0x3f35bf35,0x3f808000,0xbf353f35,0xbf80,0xbf35bf35,0xbf80,0x3f353f35,0xbf808000,0xbf353f35,0xbf808000,0x3f35bf35,0x3f80,0x3f353f35,0x3f80,0xbf35bf35,
0x3f80,0x3f800000,0x3f80,0xbf800000,0xbf80,0xbf800000,0xbf80,0x3f800000,0x3f80,0x3f800000,0x3f80,0xbf800000,0xbf80,0xbf800000,0xbf80,0x3f800000,
0x3f808000,0xbf80,0x3f808000,0x3f80,0xbf808000,0x3f80,0xbf808000,0xbf80,0x3f808000,0xbf80,0x3f808000,0x3f80,0xbf808000,0x3f80,0xbf808000,0xbf80,
0x3f80,0x3f35bf35,0x3f80,0xbf353f35,0xbf800000,0x3f353f35,0xbf800000,0xbf35bf35,0xbf80,0xbf353f35,0xbf80,0x3f35bf35,0x3f800000,0xbf35bf35,0x3f800000,0x3f353f35,
0x3f808000,0xbf35bf35,0x3f808000,0x3f353f35,0x3f80,0x3f35bf35,0x3f80,0xbf353f35,0xbf808000,0x3f353f35,0xbf808000,0xbf35bf35,0xbf80,0xbf353f35,0xbf80,0x3f35bf35,
0x3f80,0xbf353f35,0x3f80,0x3f35bf35,0xbf800000,0xbf35bf35,0xbf800000,0x3f353f35,0xbf80,0x3f35bf35,0xbf80,0xbf353f35,0x3f800000,0x3f353f35,0x3f800000,0xbf35bf35,
0xbf800000,0xbf35bf35,0xbf800000,0x3f353f35,0x8000bf80,0x3f35bf35,0x8000bf80,0xbf353f35,0x3f800000,0x3f353f35,0x3f800000,0xbf35bf35,0x80003f80,0xbf353f35,0x80003f80,0x3f35bf35,
0x3f80,0xbf800000,0x3f80,0x3f800000,0xbf80,0x3f800000,0xbf80,0xbf800000,0x3f80,0xbf800000,0x3f80,0x3f800000,0xbf80,0x3f800000,0xbf80,0xbf800000,
0xbf800000,0x8000bf80,0xbf800000,0x80003f80,0x3f800000,0x80003f80,0x3f800000,0x8000bf80,0xbf800000,0x8000bf80,0xbf800000,0x80003f80,0x3f800000,0x80003f80,0x3f800000,0x8000bf80,
0x3f80,0xbf35bf35,0x3f80,0x3f353f35,0x3f800000,0xbf353f35,0x3f800000,0x3f35bf35,0xbf80,0x3f353f35,0xbf80,0xbf35bf35,0xbf800000,0x3f35bf35,0xbf800000,0xbf353f35,
0xbf800000,0x3f35bf35,0xbf800000,0xbf353f35,0x80003f80,0xbf35bf35,0x80003f80,0x3f353f35,0x3f800000,0xbf353f35,0x3f800000,0x3f35bf35,0x8000bf80,0x3f353f35,0x8000bf80,0xbf35bf35,
0x3f80,0xbf80,0x3f80,0x3f80,0x3f80,0xbf80,0x3f80,0x3f80,0x3f80,0xbf80,0x3f80,0x3f80,0x3f80,0xbf80,0x3f80,0x3f80,
0xbf800000,0x3f800000,0xbf800000,0xbf800000,0xbf800000,0x3f800000,0xbf800000,0xbf800000,0xbf800000,0x3f800000,0xbf800000,0xbf800000,0xbf800000,0x3f800000,0xbf800000,0xbf800000,
0x3f80,0x3f80,0x3f800000,0xbf800000,0x3f80,0x3f80,0x3f800000,0xbf800000,0x3f80,0x3f80,0x3f800000,0xbf800000,0x3f80,0x3f80,0x3f800000,0xbf800000,
0x3f808000,0x3f808000,0xbf80,0x3f80,0x3f808000,0x3f808000,0xbf80,0x3f80,0x3f808000,0x3f808000,0xbf80,0x3f80,0x3f808000,0x3f808000,0xbf80,0x3f80,
0x3ec43f6d,0x3f6d3ec4,0x3f6dbec4,0xbec43f6d,0x3f6dbec4,0x3ec4bf6d,0xbec4bf6d,0x3f6d3ec4,0xbec4bf6d,0xbf6dbec4,0xbf6d3ec4,0x3ec4bf6d,0xbf6d3ec4,0xbec43f6d,0x3ec43f6d,0xbf6dbec4,
0x3f6dbec4,0x3ec4bf6d,0xbec4bf6d,0x3f6d3ec4,0xbec4bf6d,0xbf6dbec4,0xbf6d3ec4,0x3ec4bf6d,0xbf6d3ec4,0xbec43f6d,0x3ec43f6d,0xbf6dbec4,0x3ec43f6d,0x3f6d3ec4,0x3f6dbec4,0xbec43f6d,
0x3f353f35,0x3f35bf35,0x3f35bf35,0x3f353f35,0xbf35bf35,0xbf353f35,0xbf353f35,0xbf35bf35,0x3f353f35,0x3f35bf35,0x3f35bf35,0x3f353f35,0xbf35bf35,0xbf353f35,0xbf353f35,0xbf35bf35,
0x3f35bf35,0xbf35bf35,0xbf35bf35,0x3f35bf35,0xbf353f35,0x3f353f35,0x3f353f35,0xbf353f35,0x3f35bf35,0xbf35bf35,0xbf35bf35,0x3f35bf35,0xbf353f35,0x3f353f35,0x3f353f35,0xbf353f35,
0x3f6d3ec4,0xbec4bf6d,0x3ec4bf6d,0x3f6dbec4,0xbec43f6d,0x3f6dbec4,0x3f6d3ec4,0x3ec43f6d,0xbf6dbec4,0x3ec43f6d,0xbec43f6d,0xbf6d3ec4,0x3ec4bf6d,0xbf6d3ec4,0xbf6dbec4,0xbec4bf6d,
0x3ec4bf6d,0xbf6d3ec4,0xbf6dbec4,0xbec4bf6d,0x3f6d3ec4,0xbec4bf6d,0x3ec4bf6d,0x3f6dbec4,0xbec43f6d,0x3f6dbec4,0x3f6d3ec4,0x3ec43f6d,0xbf6dbec4,0x3ec43f6d,0xbec43f6d,0xbf6d3ec4,
0xbec43f6d,0xbf6d3ec4,0xbf6dbec4,0x3ec43f6d,0xbf6dbec4,0xbec4bf6d,0x3ec4bf6d,0xbf6d3ec4,0x3ec4bf6d,0x3f6dbec4,0x3f6d3ec4,0xbec4bf6d,0x3f6d3ec4,0x3ec43f6d,0xbec43f6d,0x3f6dbec4,
0xbf6dbec4,0xbec4bf6d,0x3ec4bf6d,0xbf6d3ec4,0x3ec4bf6d,0x3f6dbec4,0x3f6d3ec4,0xbec4bf6d,0x3f6d3ec4,0x3ec43f6d,0xbec43f6d,0x3f6dbec4,0xbec43f6d,0xbf6d3ec4,0xbf6dbec4,0x3ec43f6d,
0xbf353f35,0xbf35bf35,0xbf35bf35,0xbf353f35,0x3f35bf35,0x3f353f35,0x3f353f35,0x3f35bf35,0xbf353f35,0xbf35bf35,0xbf35bf35,0xbf353f35,0x3f35bf35,0x3f353f35,0x3f353f35,0x3f35bf35,
0xbf35bf35,0x3f35bf35,0x3f35bf35,0xbf35bf35,0x3f353f35,0xbf353f35,0xbf353f35,0x3f353f35,0xbf35bf35,0x3f35bf35,0x3f35bf35,0xbf35bf35,0x3f353f35,0xbf353f35,0xbf353f35,0x3f353f35,
0xbf6d3ec4,0x3ec4bf6d,0xbec4bf6d,0xbf6dbec4,0x3ec43f6d,0xbf6dbec4,0xbf6d3ec4,0xbec43f6d,0x3f6dbec4,0xbec43f6d,0x3ec43f6d,0x3f6d3ec4,0xbec4bf6d,0x3f6d3ec4,0x3f6dbec4,0x3ec4bf6d,
0xbec4bf6d,0x3f6d3ec4,0x3f6dbec4,0x3ec4bf6d,0xbf6d3ec4,0x3ec4bf6d,0xbec4bf6d,0xbf6dbec4,0x3ec43f6d,0xbf6dbec4,0xbf6d3ec4,0xbec43f6d,0x3f6dbec4,0xbec43f6d,0x3ec43f6d,0x3f6d3ec4,
0xbf800000,0x3f800000,0xbf80,0xbf80,0xbf800000,0x3f800000,0xbf80,0xbf80,0xbf800000,0x3f800000,0xbf80,0xbf80,0xbf800000,0x3f800000,0xbf80,0xbf80,
0x8000bf80,0x80003f80,0x3f800000,0x3f800000,0x8000bf80,0x80003f80,0x3f800000,0x3f800000,0x8000bf80,0x80003f80,0x3f800000,0x3f800000,0x8000bf80,0x80003f80,0x3f800000,0x3f800000,
0x80003f80,0x3f800000,0x80003f80,0x3f800000,0x80003f80,0x3f800000,0x80003f80,0x3f800000,0x80003f80,0x3f800000,0x80003f80,0x3f800000,0x80003f80,0x3f800000,0x80003f80,0x3f800000,
0x80003f80,0x3f800000,0x8000bf80,0xbf800000,0xbf353f35,0x3f353f35,0x3f35bf35,0xbf35bf35,0xbf800000,0x3f80,0x3f800000,0xbf80,0xbf35bf35,0xbf353f35,0x3f353f35,0x3f35bf35,
0x80003f80,0x3f800000,0x80003f80,0x3f800000,0xbf800000,0x3f80,0xbf800000,0x3f80,0x8000bf80,0xbf800000,0x8000bf80,0xbf800000,0x3f800000,0xbf80,0x3f800000,0xbf80,
0x80003f80,0x3f800000,0x8000bf80,0xbf800000,0xbf35bf35,0xbf353f35,0x3f353f35,0x3f35bf35,0x3f800000,0xbf80,0xbf800000,0x3f80,0xbf353f35,0x3f353f35,0x3f35bf35,0xbf35bf35,
0x80003f80,0x3f800000,0x80003f80,0x3f800000,0x8000bf80,0xbf800000,0x8000bf80,0xbf800000,0x80003f80,0x3f800000,0x80003f80,0x3f800000,0x8000bf80,0xbf800000,0x8000bf80,0xbf800000,
0x80003f80,0x3f800000,0x8000bf80,0xbf800000,0x3f35bf35,0xbf35bf35,0xbf353f35,0x3f353f35,0xbf800000,0x3f80,0x3f800000,0xbf80,0x3f353f35,0x3f35bf35,0xbf35bf35,0xbf353f35,
0x80003f80,0x3f800000,0x80003f80,0x3f800000,0x3f800000,0xbf80,0x3f800000,0xbf80,0x8000bf80,0xbf800000,0x8000bf80,0xbf800000,0xbf800000,0x3f80,0xbf800000,0x3f80,
0x80003f80,0x3f800000,0x8000bf80,0xbf800000,0x3f353f35,0x3f35bf35,0xbf35bf35,0xbf353f35,0x3f800000,0xbf80,0xbf800000,0x3f80,0x3f35bf35,0xbf35bf35,0xbf353f35,0x3f353f35,
0x3f80,0xbf800000,0x3f80,0xbf800000,0x3f80,0xbf800000,0x3f80,0xbf800000,0x3f80,0xbf800000,0x3f80,0xbf800000,0x3f80,0xbf800000,0x3f80,0xbf800000,
0xbf353f35,0xbf35bf35,0x3f35bf35,0x3f353f35,0xbf800000,0x8000bf80,0x3f800000,0x80003f80,0xbf35bf35,0x3f35bf35,0x3f353f35,0xbf353f35,0xbf80,0x3f800000,0x3f80,0xbf800000,
0xbf800000,0x8000bf80,0xbf800000,0x8000bf80,0xbf80,0x3f800000,0xbf80,0x3f800000,0x3f800000,0x80003f80,0x3f800000,0x80003f80,0x3f80,0xbf800000,0x3f80,0xbf800000,
0xbf35bf35,0x3f35bf35,0x3f353f35,0xbf353f35,0x3f800000,0x80003f80,0xbf800000,0x8000bf80,0xbf353f35,0xbf35bf35,0x3f35bf35,0x3f353f35,0xbf80,0x3f800000,0x3f80,0xbf800000,
0xbf80,0x3f800000,0xbf80,0x3f800000,0x3f80,0xbf800000,0x3f80,0xbf800000,0xbf80,0x3f800000,0xbf80,0x3f800000,0x3f80,0xbf800000,0x3f80,0xbf800000,
0x3f35bf35,0x3f353f35,0xbf353f35,0xbf35bf35,0xbf800000,0x8000bf80,0x3f800000,0x80003f80,0x3f353f35,0xbf353f35,0xbf35bf35,0x3f35bf35,0xbf80,0x3f800000,0x3f80,0xbf800000,
0x3f800000,0x80003f80,0x3f800000,0x80003f80,0xbf80,0x3f800000,0xbf80,0x3f800000,0xbf800000,0x8000bf80,0xbf800000,0x8000bf80,0x3f80,0xbf800000,0x3f80,0xbf800000,
0x3f353f35,0xbf353f35,0xbf35bf35,0x3f35bf35,0x3f800000,0x80003f80,0xbf800000,0x8000bf80,0x3f35bf35,0x3f353f35,0xbf353f35,0xbf35bf35,0xbf80,0x3f800000,0x3f80,0xbf800000,
0x80003f80,0x3f800000,0xbf800000,0x3f80,0xbec43f6d,0x3f6d3ec4,0xbf6dbec4,0xbec43f6d,0xbf353f35,0x3f353f35,0xbf35bf35,0xbf353f35,0xbf6d3ec4,0x3ec43f6d,0xbec4bf6d,0xbf6d3ec4,
0x80003f80,0x3f800000,0x3f800000,0xbf80,0xbf6d3ec4,0x3ec43f6d,0x3ec43f6d,0x3f6dbec4,0xbf35bf35,0xbf353f35,0xbf353f35,0x3f353f35,0x3ec4bf6d,0xbf6dbec4,0xbf6dbec4,0xbec43f6d,
0x80003f80,0x3f800000,0xbf800000,0x3f80,0xbf6dbec4,0xbec43f6d,0x3ec4bf6d,0xbf6dbec4,0x3f35bf35,0xbf35bf35,0x3f353f35,0x3f35bf35,0x3ec43f6d,0x3f6dbec4,0xbf6d3ec4,0x3ec43f6d,
0x80003f80,0x3f800000,0x3f800000,0xbf80,0xbec4bf6d,0xbf6d3ec4,0xbf6d3ec4,0x3ec43f6d,0x3f353f35,0x3f35bf35,0x3f35bf35,0xbf35bf35,0xbf6dbec4,0xbec43f6d,0xbec43f6d,0x3f6d3ec4,
0x80003f80,0x3f800000,0xbf800000,0x3f80,0x3ec4bf6d,0xbf6dbec4,0x3f6d3ec4,0x3ec4bf6d,0xbf353f35,0x3f353f35,0xbf35bf35,0xbf353f35,0x3f6dbec4,0xbec4bf6d,0x3ec43f6d,0x3f6dbec4,
0x80003f80,0x3f800000,0x3f800000,0xbf80,0x3f6dbec4,0xbec4bf6d,0xbec4bf6d,0xbf6d3ec4,0xbf35bf35,0xbf353f35,0xbf353f35,0x3f353f35,0xbec43f6d,0x3f6d3ec4,0x3f6d3ec4,0x3ec4bf6d,
0x80003f80,0x3f800000,0xbf800000,0x3f80,0x3f6d3ec4,0x3ec4bf6d,0xbec43f6d,0x3f6d3ec4,0x3f35bf35,0xbf35bf35,0x3f353f35,0x3f35bf35,0xbec4bf6d,0xbf6d3ec4,0x3f6dbec4,0xbec4bf6d,
0x80003f80,0x3f800000,0x3f800000,0xbf80,0x3ec43f6d,0x3f6dbec4,0x3f6dbec4,0xbec4bf6d,0x3f353f35,0x3f35bf35,0x3f35bf35,0xbf35bf35,0x3f6d3ec4,0x3ec4bf6d,0x3ec4bf6d,0xbf6dbec4,
0xbec43f6d,0xbf6dbec4,0xbf6dbec4,0x3ec4bf6d,0xbf353f35,0xbf35bf35,0xbf35bf35,0x3f35bf35,0xbf6d3ec4,0xbec4bf6d,0xbec4bf6d,0x3f6dbec4,0xbf800000,0x8000bf80,0xbf80,0x3f800000,
0xbf6d3ec4,0xbec4bf6d,0x3ec43f6d,0xbf6d3ec4,0xbf35bf35,0x3f35bf35,0xbf353f35,0xbf35bf35,0x3ec4bf6d,0x3f6d3ec4,0xbf6dbec4,0x3ec4bf6d,0x3f800000,0x80003f80,0xbf80,0x3f800000,
0xbf6dbec4,0x3ec4bf6d,0x3ec4bf6d,0x3f6d3ec4,0x3f35bf35,0x3f353f35,0x3f353f35,0xbf353f35,0x3ec43f6d,0xbf6d3ec4,0xbf6d3ec4,0xbec4bf6d,0xbf800000,0x8000bf80,0xbf80,0x3f800000,
0xbec4bf6d,0x3f6dbec4,0xbf6d3ec4,0xbec4bf6d,0x3f353f35,0xbf353f35,0x3f35bf35,0x3f353f35,0xbf6dbec4,0x3ec4bf6d,0xbec43f6d,0xbf6dbec4,0x3f800000,0x80003f80,0xbf80,0x3f800000,
0x3ec4bf6d,0x3f6d3ec4,0x3f6d3ec4,0xbec43f6d,0xbf353f35,0xbf35bf35,0xbf35bf35,0x3f35bf35,0x3f6dbec4,0x3ec43f6d,0x3ec43f6d,0xbf6d3ec4,0xbf800000,0x8000bf80,0xbf80,0x3f800000,
0x3f6dbec4,0x3ec43f6d,0xbec4bf6d,0x3f6dbec4,0xbf35bf35,0x3f35bf35,0xbf353f35,0xbf35bf35,0xbec43f6d,0xbf6dbec4,0x3f6d3ec4,0xbec43f6d,0x3f800000,0x80003f80,0xbf80,0x3f800000,
0x3f6d3ec4,0xbec43f6d,0xbec43f6d,0xbf6dbec4,0x3f35bf35,0x3f353f35,0x3f353f35,0xbf353f35,0xbec4bf6d,0x3f6dbec4,0x3f6dbec4,0x3ec43f6d,0xbf800000,0x8000bf80,0xbf80,0x3f800000,
0x3ec43f6d,0xbf6d3ec4,0x3f6dbec4,0x3ec43f6d,0x3f353f35,0xbf353f35,0x3f35bf35,0x3f353f35,0x3f6d3ec4,0xbec43f6d,0x3ec4bf6d,0x3f6d3ec4,0x3f800000,0x80003f80,0xbf80,0x3f800000,
0x3f800000,0,0x3f800000,0,0x3f800000,0,0x3f800000,0,0x3f800000,0,0x3f800000,0,0x3f800000,0,0x3f800000,0,
0x3f6c835e,0x3ec3ef15,0x3f7fec43,0x3cc90ab0,0x3f7fb10f,0x3d48fb30,0x3f7f4e6d,0x3d96a905,0x3f7ec46d,0x3dc8bd36,0x3f7e1324,0x3dfab273,0x3f7d3aac,0x3e164083,0x3f7c3b28,0x3e2f10a2,
0x3f3504f3,0x3f3504f3,0x3f7fb10f,0x3d48fb30,0x3f7ec46d,0x3dc8bd36,0x3f7d3aac,0x3e164083,0x3f7b14be,0x3e47c5c2,0x3f7853f8,0x3e78cfcc,0x3f74fa0b,0x3e94a031,0x3f710908,0x3eac7cd4,
0x3ec3ef15,0x3f6c835e,0x3f7f4e6d,0x3d96a905,0x3f7d3aac,0x3e164083,0x3f79c79d,0x3e605c13,0x3f74fa0b,0x3e94a031,0x3f6ed89e,0x3eb8442a,0x3f676bd8,0x3edae880,0x3f5ebe05,0x3efc5d27,
0,0x3f800000,0x3f7ec46d,0x3dc8bd36,0x3f7b14be,0x3e47c5c2,0x3f74fa0b,0x3e94a031,0x3f6c835e,0x3ec3ef15,0x3f61c598,0x3ef15aea,0x3f54db31,0x3f0e39da,0x3f45e403,0x3f226799,
0xbec3ef15,0x3f6c835e,0x3f7e1324,0x3dfab273,0x3f7853f8,0x3e78cfcc,0x3f6ed89e,0x3eb8442a,0x3f61c598,0x3ef15aea,0x3f514d3d,0x3f13682a,0x3f3daef9,0x3f2beb4a,0x3f273656,0x3f41d870,
0xbf3504f3,0x3f3504f3,0x3f7d3aac,0x3e164083,0x3f74fa0b,0x3e94a031,0x3f676bd8,0x3edae880,0x3f54db31,0x3f0e39da,0x3f3daef9,0x3f2beb4a,0x3f226799,0x3f45e403,0x3f039c3d,0x3f5b941a,
0xbf6c835e,0x3ec3ef15,0x3f7c3b28,0x3e2f10a2,0x3f710908,0x3eac7cd4,0x3f5ebe05,0x3efc5d27,0x3f45e403,0x3f226799,0x3f273656,0x3f41d870,0x3f039c3d,0x3f5b941a,0x3eb8442a,0x3f6ed89e,
0x3f800000,0,0x3f800000,0,0x3f800000,0,0x3f800000,0,0x3f800000,0,0x3f800000,0,0x3f800000,0,0x3f800000,0,
0x3f7b14be,0x3e47c5c2,0x3f79c79d,0x3e605c13,0x3f7853f8,0x3e78cfcc,0x3f76ba07,0x3e888e93,0x3f74fa0b,0x3e94a031,0x3f731447,0x3ea09ae5,0x3f710908,0x3eac7cd4,0x3f6ed89e,0x3eb8442a,
0x3f6c835e,0x3ec3ef15,0x3f676bd8,0x3edae880,0x3f61c598,0x3ef15aea,0x3f5b941a,0x3f039c3d,0x3f54db31,0x3f0e39da,0x3f4d9f02,0x3f187fc0,0x3f45e403,0x3f226799,0x3f3daef9,0x3f2beb4a,
0x3f54db31,0x3f0e39da,0x3f49d112,0x3f1d7fd1,0x3f3daef9,0x3f2beb4a,0x3f3085bb,0x3f396842,0x3f226799,0x3f45e403,0x3f13682a,0x3f514d3d,0x3f039c3d,0x3f5b941a,0x3ee63375,0x3f64aa59,
0x3f3504f3,0x3f3504f3,0x3f226799,0x3f45e403,0x3f0e39da,0x3f54db31,0x3ef15aea,0x3f61c598,0x3ec3ef15,0x3f6c835e,0x3e94a031,0x3f74fa0b,0x3e47c5c2,0x3f7b14be,0x3dc8bd36,0x3f7ec46d,
0x3f0e39da,0x3f54db31,0x3ee63375,0x3f64aa59,0x3eac7cd4,0x3f710908,0x3e605c13,0x3f79c79d,0x3dc8bd36,0x3f7ec46d,0xbcc90ab0,0x3f7fec43,0xbe164083,0x3f7d3aac,0xbe888e93,0x3f76ba07,
0x3ec3ef15,0x3f6c835e,0x3e78cfcc,0x3f7853f8,0x3dc8bd36,0x3f7ec46d,0xbd48fb30,0x3f7fb10f,0xbe47c5c2,0x3f7b14be,0xbeac7cd4,0x3f710908,0xbef15aea,0x3f61c598,0xbf187fc0,0x3f4d9f02,
0x3e47c5c2,0x3f7b14be,0x3cc90ab0,0x3f7fec43,0xbe164083,0x3f7d3aac,0xbea09ae5,0x3f731447,0xbef15aea,0x3f61c598,0xbf1d7fd1,0x3f49d112,0xbf3daef9,0x3f2beb4a,0xbf584853,0x3f08f59b,
0x3f7b14be,0x3e47c5c2,0x3f7ffb11,0x3c490e90,0x3f7fec43,0x3cc90ab0,0x3f7fd397,0x3d16c32c,0x3f7fb10f,0x3d48fb30,0x3f7f84ab,0x3d7b2b74,0x3f7f4e6d,0x3d96a905,0x3f7f0e58,0x3dafb680,
0x3f54db31,0x3f0e39da,0x3f7fd397,0x3d16c32c,0x3f7f4e6d,0x3d96a905,0x3f7e70b0,0x3de1bc2e,0x3f7d3aac,0x3e164083,0x3f7baccd,0x3e3b6ecf,0x3f79c79d,0x3e605c13,0x3f778bc5,0x3e827dc0,
0x3f0e39da,0x3f54db31,0x3f7f84ab,0x3d7b2b74,0x3f7e1324,0x3dfab273,0x3f7baccd,0x3e3b6ecf,0x3f7853f8,0x3e78cfcc,0x3f740bdd,0x3e9aa086,0x3f6ed89e,0x3eb8442a,0x3f68bf3c,0x3ed53641,
0x3e47c5c2,0x3f7b14be,0x3f7f0e58,0x3dafb680,0x3f7c3b28,0x3e2f10a2,0x3f778bc5,0x3e827dc0,0x3f710908,0x3eac7cd4,0x3f68bf3c,0x3ed53641,0x3f5ebe05,0x3efc5d27,0x3f531849,0x3f10d3cd,
0xbe47c5c2,0x3f7b14be,0x3f7e70b0,0x3de1bc2e,0x3f79c79d,0x3e605c13,0x3f721352,0x3ea68f12,0x3f676bd8,0x3edae880,0x3f59f26a,0x3f064b82,0x3f49d112,0x3f1d7fd1,0x3f373a23,0x3f32c8c9,
0xbf0e39da,0x3f54db31,0x3f7dabcc,0x3e09cf86,0x3f76ba07,0x3e888e93,0x3f6b4b0c,0x3ec9b953,0x3f5b941a,0x3f039c3d,0x3f47de65,0x3f1ff6cb,0x3f3085bb,0x3f396842,0x3f15f6d9,0x3f4f7a1f,
0xbf54db31,0x3f0e39da,0x3f7cbfc9,0x3e22abb6,0x3f731447,0x3ea09ae5,0x3f633c5a,0x3eebcbbb,0x3f4d9f02,0x3f187fc0,0x3f32c8c9,0x3f373a23,0x3f13682a,0x3f514d3d,0x3ee0924f,0x3f660f88,
0xbf7b14be,0x3e47c5c2,0x3f7baccd,0x3e3b6ecf,0x3f6ed89e,0x3eb8442a,0x3f59f26a,0x3f064b82,0x3f3daef9,0x3f2beb4a,0x3f1b02c6,0x3f4bbbf8,0x3ee63375,0x3f64aa59,0x3e8e9a22,0x3f75dec6,
0x3f7ec46d,0x3dc8bd36,0x3f7e70b0,0x3de1bc2e,0x3f7e1324,0x3dfab273,0x3f7dabcc,0x3e09cf86,0x3f7d3aac,0x3e164083,0x3f7cbfc9,0x3e22abb6,0x3f7c3b28,0x3e2f10a2,0x3f7baccd,0x3e3b6ecf,
0x3f74fa0b,0x3e94a031,0x3f721352,0x3ea68f12,0x3f6ed89e,0x3eb8442a,0x3f6b4b0c,0x3ec9b953,0x3f676bd8,0x3edae880,0x3f633c5a,0x3eebcbbb,0x3f5ebe05,0x3efc5d27,0x3f59f26a,0x3f064b82,
0x3f61c598,0x3ef15aea,0x3f59f26a,0x3f064b82,0x3f514d3d,0x3f13682a,0x3f47de65,0x3f1ff6cb,0x3f3daef9,0x3f2beb4a,0x3f32c8c9,0x3f373a23,0x3f273656,0x3f41d870,0x3f1b02c6,0x3f4bbbf8,
0x3f45e403,0x3f226799,0x3f373a23,0x3f32c8c9,0x3f273656,0x3f41d870,0x3f15f6d9,0x3f4f7a1f,0x3f039c3d,0x3f5b941a,0x3ee0924f,0x3f660f88,0x3eb8442a,0x3f6ed89e,0x3e8e9a22,0x3f75dec6,
0x3f226799,0x3f45e403,0x3f0b9a6b,0x3f5695e5,0x3ee63375,0x3f64aa59,0x3eb263ef,0x3f6ff573,0x3e78cfcc,0x3f7853f8,0x3e09cf86,0x3f7dabcc,0x3cc90ab0,0x3f7fec43,0xbdafb680,0x3f7f0e58,
0x3ef15aea,0x3f61c598,0x3eb263ef,0x3f6ff573,0x3e605c13,0x3f79c79d,0x3dafb680,0x3f7f0e58,0xbd48fb30,0x3f7fb10f,0xbe3b6ecf,0x3f7baccd,0xbea09ae5,0x3f731447,0xbee0924f,0x3f660f88,
0x3e94a031,0x3f74fa0b,0x3e09cf86,0x3f7dabcc,0xbcc90ab0,0x3f7fec43,0xbe3b6ecf,0x3f7baccd,0xbeac7cd4,0x3f710908,0xbef6e0cb,0x3f604621,0xbf1d7fd1,0x3f49d112,0xbf3b8f3b,0x3f2e3bde,
0x3dc8bd36,0x3f7ec46d,0xbdafb680,0x3f7f0e58,0xbe888e93,0x3f76ba07,0xbee0924f,0x3f660f88,0xbf187fc0,0x3f4d9f02,0xbf3b8f3b,0x3f2e3bde,0xbf584853,0x3f08f59b,0xbf6db293,0x3ebe1d4a,
0x3f803f80,0x80003f80,0x3f803f80,0xbec43f6d,0x80003f80,0x80003f80,0xbf353f35,0xbf6d3ec4,0x80003f80,0x80003f80,0xbf800000,0xbf6dbec4,0x80003f80,0x80003f80,0xbf35bf35,0xbec4bf6d,
0xbf803f80,0xbe483f7b,0xbf803f80,0xbf0e3f55,0xbec43f6d,0xbf0e3f55,0xbf6d3ec4,0xbf7bbe48,0xbf353f35,0xbf553f0e,0xbf35bf35,0xbe48bf7b,0xbf6d3ec4,0xbf7b3e48,0x3ec4bf6d,0x3f55bf0e,
0x3f803f80,0xbf353f35,0x3f803f80,0xbf6d3ec4,0xbf800000,0xbf35bf35,0xbf35bf35,0x3ec4bf6d,0x8000bf80,0x3f35bf35,0x3f800000,0x3ec43f6d,0x3f800000,0x3f353f35,0xbf353f35,0xbf6dbec4,
0xbf803f80,0xbf553f0e,0xbf803f80,0xbf7b3e48,0xbf6dbec4,0xbe48bf7b,0xbec4bf6d,0x3f55bf0e,0x3f35bf35,0x3f7b3e48,0x3f353f35,0xbf0e3f55,0x3ec43f6d,0xbf0e3f55,0xbf6dbec4,0x3e48bf7b,
0x3f803f80,0xbf800000,0x3f803f80,0xbf6dbec4,0x8000bf80,0x3f800000,0x3f35bf35,0x3ec43f6d,0x80003f80,0xbf800000,0xbf800000,0x3ec4bf6d,0x8000bf80,0x3f800000,0x3f353f35,0xbf6d3ec4,
0xbf803f80,0xbf7bbe48,0xbf803f80,0xbf55bf0e,0x3ec4bf6d,0x3f553f0e,0x3f6dbec4,0xbe483f7b,0xbf353f35,0xbf0ebf55,0xbf35bf35,0x3f7bbe48,0x3f6dbec4,0x3e483f7b,0xbec43f6d,0xbf0ebf55,
0x3f803f80,0xbf35bf35,0x3f803f80,0xbec4bf6d,0x3f800000,0xbf353f35,0x3f353f35,0xbf6dbec4,0x8000bf80,0x3f353f35,0x3f800000,0xbf6d3ec4,0xbf800000,0x3f35bf35,0x3f35bf35,0xbec43f6d,
0xbf803f80,0xbf0ebf55,0xbf803f80,0xbe48bf7b,0x3f6d3ec4,0xbf7b3e48,0x3ec43f6d,0xbf0ebf55,0x3f35bf35,0xbe483f7b,0x3f353f35,0xbf55bf0e,0xbec4bf6d,0x3f553f0e,0x3f6d3ec4,0xbf7bbe48,
0x3f803f80,0x8000bf80,0x3f803f80,0x3ec4bf6d,0x80003f80,0x8000bf80,0xbf353f35,0x3f6dbec4,0x80003f80,0x8000bf80,0xbf800000,0x3f6d3ec4,0x80003f80,0x8000bf80,0xbf35bf35,0x3ec43f6d,
0xbf803f80,0x3e48bf7b,0xbf803f80,0x3f0ebf55,0xbec43f6d,0x3f0ebf55,0xbf6d3ec4,0x3f7b3e48,0xbf353f35,0x3f55bf0e,0xbf35bf35,0x3e483f7b,0xbf6d3ec4,0x3f7bbe48,0x3ec4bf6d,0xbf553f0e,
0x3f803f80,0x3f35bf35,0x3f803f80,0x3f6dbec4,0xbf800000,0x3f353f35,0xbf35bf35,0xbec43f6d,0x8000bf80,0xbf353f35,0x3f800000,0xbec4bf6d,0x3f800000,0xbf35bf35,0xbf353f35,0x3f6d3ec4,
0xbf803f80,0x3f55bf0e,0xbf803f80,0x3f7bbe48,0xbf6dbec4,0x3e483f7b,0xbec4bf6d,0xbf553f0e,0x3f35bf35,0xbf7bbe48,0x3f353f35,0x3f0ebf55,0x3ec43f6d,0x3f0ebf55,0xbf6dbec4,0xbe483f7b,
0x3f803f80,0x3f800000,0x3f803f80,0x3f6d3ec4,0x8000bf80,0xbf800000,0x3f35bf35,0xbec4bf6d,0x80003f80,0x3f800000,0xbf800000,0xbec43f6d,0x8000bf80,0xbf800000,0x3f353f35,0x3f6dbec4,
0xbf803f80,0x3f7b3e48,0xbf803f80,0x3f553f0e,0x3ec4bf6d,0xbf55bf0e,0x3f6dbec4,0x3e48bf7b,0xbf353f35,0x3f0e3f55,0xbf35bf35,0xbf7b3e48,0x3f6dbec4,0xbe48bf7b,0xbec43f6d,0x3f0e3f55,
0x3f803f80,0x3f353f35,0x3f803f80,0x3ec43f6d,0x3f800000,0x3f35bf35,0x3f353f35,0x3f6d3ec4,0x8000bf80,0xbf35bf35,0x3f800000,0x3f6dbec4,0xbf800000,0xbf353f35,0x3f35bf35,0x3ec4bf6d,
0xbf803f80,0x3f0e3f55,0xbf803f80,0x3e483f7b,0x3f6d3ec4,0x3f7bbe48,0x3ec43f6d,0x3f0e3f55,0x3f35bf35,0x3e48bf7b,0x3f353f35,0x3f553f0e,0xbec4bf6d,0xbf55bf0e,0x3f6d3ec4,0x3f7b3e48,
0x80003f80,0x80003f80,0x8000bf80,0x3ec4bf6d,0x80003f80,0x80003f80,0x3f35bf35,0x3f6dbec4,0x80003f80,0x80003f80,0x3f800000,0x3f6d3ec4,0x80003f80,0x80003f80,0x3f353f35,0x3ec43f6d,
0xbf800000,0xbf7bbe48,0x3f800000,0x3f553f0e,0xbf6dbec4,0xbf55bf0e,0x3ec43f6d,0xbe483f7b,0xbf35bf35,0xbf0ebf55,0xbf353f35,0xbf7b3e48,0xbec4bf6d,0xbe48bf7b,0xbf6dbec4,0xbf0ebf55,
0x80003f80,0xbf353f35,0x8000bf80,0x3f6dbec4,0xbf800000,0xbf35bf35,0x3f353f35,0xbec43f6d,0x8000bf80,0x3f35bf35,0xbf800000,0xbec4bf6d,0x3f800000,0x3f353f35,0x3f35bf35,0x3f6d3ec4,
0xbf800000,0xbf0ebf55,0x3f800000,0x3e483f7b,0x3ec4bf6d,0x3f7bbe48,0xbf6d3ec4,0xbf0ebf55,0x3f353f35,0xbe483f7b,0x3f35bf35,0x3f553f0e,0xbf6d3ec4,0xbf55bf0e,0xbec43f6d,0xbf7bbe48,
0x80003f80,0xbf800000,0x8000bf80,0x3f6d3ec4,0x8000bf80,0x3f800000,0xbf353f35,0xbec4bf6d,0x80003f80,0xbf800000,0x3f800000,0xbec43f6d,0x8000bf80,0x3f800000,0xbf35bf35,0x3f6dbec4,
0xbf800000,0x3e48bf7b,0x3f800000,0xbf0e3f55,0x3f6d3ec4,0xbf0e3f55,0xbec4bf6d,0x3f7b3e48,0xbf35bf35,0x3f55bf0e,0xbf353f35,0xbe48bf7b,0x3ec43f6d,0xbf7b3e48,0x3f6d3ec4,0xbf553f0e,
0x80003f80,0xbf35bf35,0x8000bf80,0x3ec43f6d,0x3f800000,0xbf353f35,0xbf35bf35,0x3f6d3ec4,0x8000bf80,0x3f353f35,0xbf800000,0x3f6dbec4,0xbf800000,0x3f35bf35,0xbf353f35,0x3ec4bf6d,
0xbf800000,0x3f55bf0e,0x3f800000,0xbf7b3e48,0xbec43f6d,0xbe48bf7b,0x3f6dbec4,0xbf553f0e,0x3f353f35,0xbf7bbe48,0x3f35bf35,0xbf0e3f55,0x3f6dbec4,0xbf0e3f55,0x3ec4bf6d,0xbe483f7b,
0x80003f80,0x8000bf80,0x8000bf80,0xbec43f6d,0x80003f80,0x8000bf80,0x3f35bf35,0xbf6d3ec4,0x80003f80,0x8000bf80,0x3f800000,0xbf6dbec4,0x80003f80,0x8000bf80,0x3f353f35,0xbec4bf6d,
0xbf800000,0x3f7b3e48,0x3f800000,0xbf55bf0e,0xbf6dbec4,0x3f553f0e,0x3ec43f6d,0x3e48bf7b,0xbf35bf35,0x3f0e3f55,0xbf353f35,0x3f7bbe48,0xbec4bf6d,0x3e483f7b,0xbf6dbec4,0x3f0e3f55,
0x80003f80,0x3f35bf35,0x8000bf80,0xbf6d3ec4,0xbf800000,0x3f353f35,0x3f353f35,0x3ec4bf6d,0x8000bf80,0xbf353f35,0xbf800000,0x3ec43f6d,0x3f800000,0xbf35bf35,0x3f35bf35,0xbf6dbec4,
0xbf800000,0x3f0e3f55,0x3f800000,0xbe48bf7b,0x3ec4bf6d,0xbf7b3e48,0xbf6d3ec4,0x3f0e3f55,0x3f353f35,0x3e48bf7b,0x3f35bf35,0xbf55bf0e,0xbf6d3ec4,0x3f553f0e,0xbec43f6d,0x3f7b3e48,
0x80003f80,0x3f800000,0x8000bf80,0xbf6dbec4,0x8000bf80,0xbf800000,0xbf353f35,0x3ec43f6d,0x80003f80,0x3f800000,0x3f800000,0x3ec4bf6d,0x8000bf80,0xbf800000,0xbf35bf35,0xbf6d3ec4,
0xbf800000,0xbe483f7b,0x3f800000,0x3f0ebf55,0x3f6d3ec4,0x3f0ebf55,0xbec4bf6d,0xbf7bbe48,0xbf35bf35,0xbf553f0e,0xbf353f35,0x3e483f7b,0x3ec43f6d,0x3f7bbe48,0x3f6d3ec4,0x3f55bf0e,
0x80003f80,0x3f353f35,0x8000bf80,0xbec4bf6d,0x3f800000,0x3f35bf35,0xbf35bf35,0xbf6dbec4,0x8000bf80,0xbf35bf35,0xbf800000,0xbf6d3ec4,0xbf800000,0xbf353f35,0xbf353f35,0xbec43f6d,
0xbf800000,0xbf553f0e,0x3f800000,0x3f7bbe48,0xbec43f6d,0x3e483f7b,0x3f6dbec4,0x3f55bf0e,0x3f353f35,0x3f7b3e48,0x3f35bf35,0x3f0ebf55,0x3f6dbec4,0x3f0ebf55,0x3ec4bf6d,0x3e48bf7b,
0x3f80,0x3f80,0x3f80,0x3f80,0x3f80,0x3f80,0x3f800000,0x3f800000,0x3f80,0x3f80,0xbf80,0xbf80,0x3f80,0x3f80,0xbf800000,0xbf800000,
0x3f808000,0x3f808000,0x3f808000,0x3f808000,0x3f808000,0x3f808000,0xbf80,0xbf80,0x3f808000,0x3f808000,0xbf808000,0xbf808000,0x3f808000,0x3f808000,0x3f80,0x3f80,
0x3f80,0x3f800000,0x3f80,0x3f800000,0x3ec43f6d,0x3f6dbec4,0x3f6dbec4,0xbec4bf6d,0x3f353f35,0x3f35bf35,0xbf35bf35,0xbf353f35,0x3f6d3ec4,0x3ec4bf6d,0xbec43f6d,0x3f6d3ec4,
0x3f808000,0xbf80,0x3f808000,0xbf80,0x3f6dbec4,0xbec4bf6d,0xbec4bf6d,0xbf6d3ec4,0x3f35bf35,0xbf35bf35,0xbf353f35,0x3f353f35,0x3ec4bf6d,0xbf6dbec4,0x3f6d3ec4,0x3ec4bf6d,
0x3f80,0xbf80,0x3f80,0xbf80,0x3f353f35,0xbf35bf35,0x3f35bf35,0xbf353f35,0x3f800000,0xbf800000,0xbf800000,0x3f800000,0x3f35bf35,0xbf353f35,0x3f353f35,0xbf35bf35,
0x3f808000,0xbf808000,0x3f808000,0xbf808000,0x3f35bf35,0xbf353f35,0xbf35bf35,0x3f353f35,0xbf80,0x3f80,0x3f80,0xbf80,0xbf35bf35,0x3f353f35,0x3f35bf35,0xbf353f35,
0x3f80,0xbf800000,0x3f80,0xbf800000,0x3f6d3ec4,0xbec43f6d,0x3ec4bf6d,0x3f6d3ec4,0x3f35bf35,0x3f353f35,0xbf353f35,0xbf35bf35,0xbec4bf6d,0x3f6dbec4,0x3f6dbec4,0x3ec43f6d,
0x3f808000,0x3f80,0x3f808000,0x3f80,0x3ec4bf6d,0x3f6d3ec4,0xbf6dbec4,0x3ec4bf6d,0xbf35bf35,0x3f35bf35,0x3f353f35,0xbf353f35,0xbf6d3ec4,0xbec4bf6d,0xbec4bf6d,0x3f6dbec4,
0x3f80,0x3f80,0x3f80,0x3f80,0xbf80,0xbf80,0xbf800000,0xbf800000,0x3f80,0x3f80,0xbf80,0xbf80,0xbf80,0xbf80,0x3f800000,0x3f800000,
0x3f808000,0x3f808000,0x3f808000,0x3f808000,0xbf808000,0xbf808000,0x3f80,0x3f80,0x3f808000,0x3f808000,0xbf808000,0xbf808000,0xbf808000,0xbf808000,0xbf80,0xbf80,
0x3f80,0x3f800000,0x3f80,0x3f800000,0xbec4bf6d,0xbf6d3ec4,0xbf6d3ec4,0x3ec43f6d,0x3f353f35,0x3f35bf35,0xbf35bf35,0xbf353f35,0xbf6dbec4,0xbec43f6d,0x3ec4bf6d,0xbf6dbec4,
0x3f808000,0xbf80,0x3f808000,0xbf80,0xbf6d3ec4,0x3ec43f6d,0x3ec43f6d,0x3f6dbec4,0x3f35bf35,0xbf35bf35,0xbf353f35,0x3f353f35,0xbec43f6d,0x3f6d3ec4,0xbf6dbec4,0xbec43f6d,
0x3f80,0xbf80,0x3f80,0xbf80,0xbf35bf35,0x3f353f35,0xbf353f35,0x3f35bf35,0x3f800000,0xbf800000,0xbf800000,0x3f800000,0xbf353f35,0x3f35bf35,0xbf35bf35,0x3f353f35,
0x3f808000,0xbf808000,0x3f808000,0xbf808000,0xbf353f35,0x3f35bf35,0x3f353f35,0xbf35bf35,0xbf80,0x3f80,0x3f80,0xbf80,0x3f353f35,0xbf35bf35,0xbf353f35,0x3f35bf35,
0x3f80,0xbf800000,0x3f80,0xbf800000,0xbf6dbec4,0x3ec4bf6d,0xbec43f6d,0xbf6dbec4,0x3f35bf35,0x3f353f35,0xbf353f35,0xbf35bf35,0x3ec43f6d,0xbf6d3ec4,0xbf6d3ec4,0xbec4bf6d,
0x3f808000,0x3f80,0x3f808000,0x3f80,0xbec43f6d,0xbf6dbec4,0x3f6d3ec4,0xbec43f6d,0xbf35bf35,0x3f35bf35,0x3f353f35,0xbf353f35,0x3f6dbec4,0x3ec43f6d,0x3ec43f6d,0xbf6d3ec4,
0x3f80,0x3f80,0x3f80,0x3f80,0x3f80,0x3f80,0x3f800000,0x3f800000,0x3f80,0x3f80,0xbf80,0xbf80,0x3f80,0x3f80,0xbf800000,0xbf800000,
0x3f808000,0x3f808000,0x3f808000,0x3f808000,0x3f808000,0x3f808000,0xbf80,0xbf80,0x3f808000,0x3f808000,0xbf808000,0xbf808000,0x3f808000,0x3f808000,0x3f80,0x3f80,
0xbf80,0xbf800000,0xbf80,0xbf800000,0xbec4bf6d,0xbf6d3ec4,0xbf6d3ec4,0x3ec43f6d,0xbf35bf35,0xbf353f35,0x3f353f35,0x3f35bf35,0xbf6dbec4,0xbec43f6d,0x3ec4bf6d,0xbf6dbec4,
0xbf808000,0x3f80,0xbf808000,0x3f80,0xbf6d3ec4,0x3ec43f6d,0x3ec43f6d,0x3f6dbec4,0xbf353f35,0x3f353f35,0x3f35bf35,0xbf35bf35,0xbec43f6d,0x3f6d3ec4,0xbf6dbec4,0xbec43f6d,
0x3f80,0xbf80,0x3f80,0xbf80,0x3f353f35,0xbf35bf35,0x3f35bf35,0xbf353f35,0x3f800000,0xbf800000,0xbf800000,0x3f800000,0x3f35bf35,0xbf353f35,0x3f353f35,0xbf35bf35,
0x3f808000,0xbf808000,0x3f808000,0xbf808000,0x3f35bf35,0xbf353f35,0xbf35bf35,0x3f353f35,0xbf80,0x3f80,0x3f80,0xbf80,0xbf35bf35,0x3f353f35,0x3f35bf35,0xbf353f35,
0xbf80,0x3f800000,0xbf80,0x3f800000,0xbf6dbec4,0x3ec4bf6d,0xbec43f6d,0xbf6dbec4,0xbf353f35,0xbf35bf35,0x3f35bf35,0x3f353f35,0x3ec43f6d,0xbf6d3ec4,0xbf6d3ec4,0xbec4bf6d,
0xbf808000,0xbf80,0xbf808000,0xbf80,0xbec43f6d,0xbf6dbec4,0x3f6d3ec4,0xbec43f6d,0x3f353f35,0xbf353f35,0xbf35bf35,0x3f35bf35,0x3f6dbec4,0x3ec43f6d,0x3ec43f6d,0xbf6d3ec4,
0x3f80,0x3f80,0x3f80,0x3f80,0xbf80,0xbf80,0xbf800000,0xbf800000,0x3f80,0x3f80,0xbf80,0xbf80,0xbf80,0xbf80,0x3f800000,0x3f800000,
0x3f808000,0x3f808000,0x3f808000,0x3f808000,0xbf808000,0xbf808000,0x3f80,0x3f80,0x3f808000,0x3f808000,0xbf808000,0xbf808000,0xbf808000,0xbf808000,0xbf80,0xbf80,
0xbf80,0xbf800000,0xbf80,0xbf800000,0x3ec43f6d,0x3f6dbec4,0x3f6dbec4,0xbec4bf6d,0xbf35bf35,0xbf353f35,0x3f353f35,0x3f35bf35,0x3f6d3ec4,0x3ec4bf6d,0xbec43f6d,0x3f6d3ec4,
0xbf808000,0x3f80,0xbf808000,0x3f80,0x3f6dbec4,0xbec4bf6d,0xbec4bf6d,0xbf6d3ec4,0xbf353f35,0x3f353f35,0x3f35bf35,0xbf35bf35,0x3ec4bf6d,0xbf6dbec4,0x3f6d3ec4,0x3ec4bf6d,
0x3f80,0xbf80,0x3f80,0xbf80,0xbf35bf35,0x3f353f35,0xbf353f35,0x3f35bf35,0x3f800000,0xbf800000,0xbf800000,0x3f800000,0xbf353f35,0x3f35bf35,0xbf35bf35,0x3f353f35,
0x3f808000,0xbf808000,0x3f808000,0xbf808000,0xbf353f35,0x3f35bf35,0x3f353f35,0xbf35bf35,0xbf80,0x3f80,0x3f80,0xbf80,0x3f353f35,0xbf35bf35,0xbf353f35,0x3f35bf35,
0xbf80,0x3f800000,0xbf80,0x3f800000,0x3f6d3ec4,0xbec43f6d,0x3ec4bf6d,0x3f6d3ec4,0xbf353f35,0xbf35bf35,0x3f35bf35,0x3f353f35,0xbec4bf6d,0x3f6dbec4,0x3f6dbec4,0x3ec43f6d,
0xbf808000,0xbf80,0xbf808000,0xbf80,0x3ec4bf6d,0x3f6d3ec4,0xbf6dbec4,0x3ec4bf6d,0x3f353f35,0xbf353f35,0xbf35bf35,0x3f35bf35,0xbf6d3ec4,0xbec4bf6d,0xbec4bf6d,0x3f6dbec4,
0x80003f80,0x80003f80,0x80003f80,0xbf800000,0x80003f80,0x80003f80,0x8000bf80,0x3f800000,0x80003f80,0x80003f80,0x80003f80,0xbf800000,0x80003f80,0x80003f80,0x8000bf80,0x3f800000,
0x3f800000,0x3f800000,0x3f800000,0x3f80,0x3f800000,0x3f800000,0xbf800000,0xbf80,0x3f800000,0x3f800000,0x3f800000,0x3f80,0x3f800000,0x3f800000,0xbf800000,0xbf80,
0x80003f80,0xbec43f6d,0x80003f80,0xbf6dbec4,0xbf353f35,0xbf6d3ec4,0x3f35bf35,0x3ec43f6d,0xbf800000,0xbf6dbec4,0xbf800000,0x3ec4bf6d,0xbf35bf35,0xbec4bf6d,0x3f353f35,0xbf6d3ec4,
0x3f800000,0x3f6d3ec4,0x3f800000,0xbec43f6d,0x3f353f35,0x3ec43f6d,0xbf35bf35,0x3f6dbec4,0x3f80,0xbec43f6d,0x3f80,0xbf6dbec4,0xbf353f35,0xbf6d3ec4,0x3f35bf35,0x3ec43f6d,
0x80003f80,0xbf353f35,0x80003f80,0xbf35bf35,0xbf800000,0xbf35bf35,0x3f800000,0xbf353f35,0x8000bf80,0x3f35bf35,0x8000bf80,0x3f353f35,0x3f800000,0x3f353f35,0xbf800000,0x3f35bf35,
0x3f800000,0x3f353f35,0x3f800000,0xbf353f35,0x3f80,0xbf353f35,0xbf80,0x3f353f35,0xbf800000,0xbf35bf35,0xbf800000,0x3f35bf35,0xbf80,0x3f35bf35,0x3f80,0xbf35bf35,
0x80003f80,0xbf6d3ec4,0x80003f80,0xbec4bf6d,0xbf35bf35,0x3ec4bf6d,0x3f353f35,0xbf6dbec4,0x3f800000,0x3ec43f6d,0x3f800000,0xbf6d3ec4,0xbf353f35,0xbf6dbec4,0x3f35bf35,0xbec43f6d,
0x3f800000,0x3ec43f6d,0x3f800000,0xbf6d3ec4,0xbf353f35,0xbf6dbec4,0x3f35bf35,0xbec43f6d,0xbf80,0x3f6dbec4,0xbf80,0x3ec43f6d,0x3f353f35,0xbec43f6d,0xbf35bf35,0x3f6d3ec4,
0x80003f80,0x8000bf80,0x80003f80,0x3f800000,0x80003f80,0x8000bf80,0x8000bf80,0xbf800000,0x80003f80,0x8000bf80,0x80003f80,0x3f800000,0x80003f80,0x8000bf80,0x8000bf80,0xbf800000,
0x3f800000,0xbf800000,0x3f800000,0xbf80,0x3f800000,0xbf800000,0xbf800000,0x3f80,0x3f800000,0xbf800000,0x3f800000,0xbf80,0x3f800000,0xbf800000,0xbf800000,0x3f80,
0x80003f80,0x3ec4bf6d,0x80003f80,0x3f6d3ec4,0xbf353f35,0x3f6dbec4,0x3f35bf35,0xbec4bf6d,0xbf800000,0x3f6d3ec4,0xbf800000,0xbec43f6d,0xbf35bf35,0x3ec43f6d,0x3f353f35,0x3f6dbec4,
0x3f800000,0xbf6dbec4,0x3f800000,0x3ec4bf6d,0x3f353f35,0xbec4bf6d,0xbf35bf35,0xbf6d3ec4,0x3f80,0x3ec4bf6d,0x3f80,0x3f6d3ec4,0xbf353f35,0x3f6dbec4,0x3f35bf35,0xbec4bf6d,
0x80003f80,0x3f35bf35,0x80003f80,0x3f353f35,0xbf800000,0x3f353f35,0x3f800000,0x3f35bf35,0x8000bf80,0xbf353f35,0x8000bf80,0xbf35bf35,0x3f800000,0xbf35bf35,0xbf800000,0xbf353f35,
0x3f800000,0xbf35bf35,0x3f800000,0x3f35bf35,0x3f80,0x3f35bf35,0xbf80,0xbf35bf35,0xbf800000,0x3f353f35,0xbf800000,0xbf353f35,0xbf80,0xbf353f35,0x3f80,0x3f353f35,
0x80003f80,0x3f6dbec4,0x80003f80,0x3ec43f6d,0xbf35bf35,0xbec43f6d,0x3f353f35,0x3f6d3ec4,0x3f800000,0xbec4bf6d,0x3f800000,0x3f6dbec4,0xbf353f35,0x3f6d3ec4,0x3f35bf35,0x3ec4bf6d,
0x3f800000,0xbec4bf6d,0x3f800000,0x3f6dbec4,0xbf353f35,0x3f6d3ec4,0x3f35bf35,0x3ec4bf6d,0xbf80,0xbf6d3ec4,0xbf80,0xbec4bf6d,0x3f353f35,0x3ec4bf6d,0xbf35bf35,0xbf6dbec4,
0x80003f80,0x80003f80,0x80003f80,0xbf800000,0x80003f80,0x80003f80,0x8000bf80,0x3f800000,0x80003f80,0x80003f80,0x80003f80,0xbf800000,0x80003f80,0x80003f80,0x8000bf80,0x3f800000,
0x3f800000,0x3f800000,0x3f800000,0x3f80,0x3f800000,0x3f800000,0xbf800000,0xbf80,0x3f800000,0x3f800000,0x3f800000,0x3f80,0x3f800000,0x3f800000,0xbf800000,0xbf80,
0x8000bf80,0x3ec4bf6d,0x8000bf80,0x3f6d3ec4,0x3f35bf35,0x3f6dbec4,0xbf353f35,0xbec4bf6d,0x3f800000,0x3f6d3ec4,0x3f800000,0xbec43f6d,0x3f353f35,0x3ec43f6d,0xbf35bf35,0x3f6dbec4,
0xbf800000,0xbf6dbec4,0xbf800000,0x3ec4bf6d,0xbf35bf35,0xbec4bf6d,0x3f353f35,0xbf6d3ec4,0xbf80,0x3ec4bf6d,0xbf80,0x3f6d3ec4,0x3f35bf35,0x3f6dbec4,0xbf353f35,0xbec4bf6d,
0x80003f80,0xbf353f35,0x80003f80,0xbf35bf35,0xbf800000,0xbf35bf35,0x3f800000,0xbf353f35,0x8000bf80,0x3f35bf35,0x8000bf80,0x3f353f35,0x3f800000,0x3f353f35,0xbf800000,0x3f35bf35,
0x3f800000,0x3f353f35,0x3f800000,0xbf353f35,0x3f80,0xbf353f35,0xbf80,0x3f353f35,0xbf800000,0xbf35bf35,0xbf800000,0x3f35bf35,0xbf80,0x3f35bf35,0x3f80,0xbf35bf35,
0x8000bf80,0x3f6dbec4,0x8000bf80,0x3ec43f6d,0x3f353f35,0xbec43f6d,0xbf35bf35,0x3f6d3ec4,0xbf800000,0xbec4bf6d,0xbf800000,0x3f6dbec4,0x3f35bf35,0x3f6d3ec4,0xbf353f35,0x3ec4bf6d,
0xbf800000,0xbec4bf6d,0xbf800000,0x3f6dbec4,0x3f35bf35,0x3f6d3ec4,0xbf353f35,0x3ec4bf6d,0x3f80,0xbf6d3ec4,0x3f80,0xbec4bf6d,0xbf35bf35,0x3ec4bf6d,0x3f353f35,0xbf6dbec4,
0x80003f80,0x8000bf80,0x80003f80,0x3f800000,0x80003f80,0x8000bf80,0x8000bf80,0xbf800000,0x80003f80,0x8000bf80,0x80003f80,0x3f800000,0x80003f80,0x8000bf80,0x8000bf80,0xbf800000,
0x3f800000,0xbf800000,0x3f800000,0xbf80,0x3f800000,0xbf800000,0xbf800000,0x3f80,0x3f800000,0xbf800000,0x3f800000,0xbf80,0x3f800000,0xbf800000,0xbf800000,0x3f80,
0x8000bf80,0xbec43f6d,0x8000bf80,0xbf6dbec4,0x3f35bf35,0xbf6d3ec4,0xbf353f35,0x3ec43f6d,0x3f800000,0xbf6dbec4,0x3f800000,0x3ec4bf6d,0x3f353f35,0xbec4bf6d,0xbf35bf35,0xbf6d3ec4,
0xbf800000,0x3f6d3ec4,0xbf800000,0xbec43f6d,0xbf35bf35,0x3ec43f6d,0x3f353f35,0x3f6dbec4,0xbf80,0xbec43f6d,0xbf80,0xbf6dbec4,0x3f35bf35,0xbf6d3ec4,0xbf353f35,0x3ec43f6d,
0x80003f80,0x3f35bf35,0x80003f80,0x3f353f35,0xbf800000,0x3f353f35,0x3f800000,0x3f35bf35,0x8000bf80,0xbf353f35,0x8000bf80,0xbf35bf35,0x3f800000,0xbf35bf35,0xbf800000,0xbf353f35,
0x3f800000,0xbf35bf35,0x3f800000,0x3f35bf35,0x3f80,0x3f35bf35,0xbf80,0xbf35bf35,0xbf800000,0x3f353f35,0xbf800000,0xbf353f35,0xbf80,0xbf353f35,0x3f80,0x3f353f35,
0x8000bf80,0xbf6d3ec4,0x8000bf80,0xbec4bf6d,0x3f353f35,0x3ec4bf6d,0xbf35bf35,0xbf6dbec4,0xbf800000,0x3ec43f6d,0xbf800000,0xbf6d3ec4,0x3f35bf35,0xbf6dbec4,0xbf353f35,0xbec43f6d,
0xbf800000,0x3ec43f6d,0xbf800000,0xbf6d3ec4,0x3f35bf35,0xbf6dbec4,0xbf353f35,0xbec43f6d,0x3f80,0x3f6dbec4,0x3f80,0x3ec43f6d,0xbf35bf35,0xbec43f6d,0x3f353f35,0x3f6d3ec4,
0x3f80,0x3f80,0x3f80,0x3f80,0x3f80,0x3f80,0xbf80,0xbf80,0x3f80,0x3f80,0x3f80,0x3f80,0x3f80,0x3f80,0xbf80,0xbf80,
0x3f808000,0x3f808000,0x3f808000,0x3f808000,0x3f808000,0x3f808000,0xbf808000,0xbf808000,0x3f808000,0x3f808000,0x3f808000,0x3f808000,0x3f808000,0x3f808000,0xbf808000,0xbf808000,
0x3f80,0xbf80,0x3f80,0xbf80,0x3f353f35,0xbf35bf35,0xbf35bf35,0x3f353f35,0x3f800000,0xbf800000,0x3f800000,0xbf800000,0x3f35bf35,0xbf353f35,0xbf353f35,0x3f35bf35,
0x3f808000,0xbf808000,0x3f808000,0xbf808000,0x3f35bf35,0xbf353f35,0xbf353f35,0x3f35bf35,0xbf80,0x3f80,0xbf80,0x3f80,0xbf35bf35,0x3f353f35,0x3f353f35,0xbf35bf35,
0x3f80,0x3f80,0x3f80,0x3f80,0x3f800000,0x3f800000,0xbf800000,0xbf800000,0xbf80,0xbf80,0xbf80,0xbf80,0xbf800000,0xbf800000,0x3f800000,0x3f800000,
0x3f808000,0x3f808000,0x3f808000,0x3f808000,0xbf80,0xbf80,0x3f80,0x3f80,0xbf808000,0xbf808000,0xbf808000,0xbf808000,0x3f80,0x3f80,0xbf80,0xbf80,
0x3f80,0xbf80,0x3f80,0xbf80,0x3f35bf35,0xbf353f35,0xbf353f35,0x3f35bf35,0xbf800000,0x3f800000,0xbf800000,0x3f800000,0x3f353f35,0xbf35bf35,0xbf35bf35,0x3f353f35,
0x3f808000,0xbf808000,0x3f808000,0xbf808000,0xbf35bf35,0x3f353f35,0x3f353f35,0xbf35bf35,0x3f80,0xbf80,0x3f80,0xbf80,0x3f35bf35,0xbf353f35,0xbf353f35,0x3f35bf35,
0x80003600,0x80003600,0x80003600,0x80003600,0x80003600,0x80003600,0x8000b600,0x8000b600,0x80003600,0x80003600,0x80003600,0x80003600,0x80003600,0x80003600,0x8000b600,0x8000b600,
0x36000000,0x36000000,0x36000000,0x36000000,0x36000000,0x36000000,0xb6000000,0xb6000000,0x36000000,0x36000000,0x36000000,0x36000000,0x36000000,0x36000000,0xb6000000,0xb6000000,
0x80003600,0x8000b600,0x80003600,0x8000b600,0xb5b535b5,0x35b5b5b5,0x35b5b5b5,0xb5b535b5,0xb6000000,0x36000000,0xb6000000,0x36000000,0xb5b5b5b5,0x35b535b5,0x35b535b5,0xb5b5b5b5,
0x36000000,0xb6000000,0x36000000,0xb6000000,0x35b535b5,0xb5b5b5b5,0xb5b5b5b5,0x35b535b5,0x3600,0xb600,0x3600,0xb600,0xb5b535b5,0x35b5b5b5,0x35b5b5b5,0xb5b535b5,
0x80003600,0x80003600,0x80003600,0x80003600,0xb6000000,0xb6000000,0x36000000,0x36000000,0x8000b600,0x8000b600,0x8000b600,0x8000b600,0x36000000,0x36000000,0xb6000000,0xb6000000,
0x36000000,0x36000000,0x36000000,0x36000000,0x3600,0x3600,0xb600,0xb600,0xb6000000,0xb6000000,0xb6000000,0xb6000000,0xb600,0xb600,0x3600,0x3600,
0x80003600,0x8000b600,0x80003600,0x8000b600,0xb5b5b5b5,0x35b535b5,0x35b535b5,0xb5b5b5b5,0x36000000,0xb6000000,0x36000000,0xb6000000,0xb5b535b5,0x35b5b5b5,0x35b5b5b5,0xb5b535b5,
0x36000000,0xb6000000,0x36000000,0xb6000000,0xb5b535b5,0x35b5b5b5,0x35b5b5b5,0xb5b535b5,0xb600,0x3600,0xb600,0x3600,0x35b535b5,0xb5b5b5b5,0xb5b5b5b5,0x35b535b5,
0x3f80,0x3e483f7b,0x3f80,0x3e483f7b,0x3d493f80,0x3e793f78,0xbd49bf80,0xbe79bf78,0x3dc93f7f,0x3e953f75,0x3dc93f7f,0x3e953f75,0x3e163f7d,0x3eac3f71,0xbe16bf7d,0xbeacbf71,
0x3f808000,0x3f7bbe48,0x3f808000,0x3f7bbe48,0x3f80bd49,0x3f78be79,0xbf803d49,0xbf783e79,0x3f7fbdc9,0x3f75be95,0x3f7fbdc9,0x3f75be95,0x3f7dbe16,0x3f71beac,0xbf7d3e16,0xbf713eac,
0x3f80,0xbe48bf7b,0x3f80,0xbe48bf7b,0x3f3e3f2c,0xbf5cbf04,0xbf3ebf2c,0x3f5c3f04,0x3f7fbdc9,0xbf753e95,0x3f7fbdc9,0xbf753e95,0x3f18bf4e,0xbedb3f67,0xbf183f4e,0x3edbbf67,
0x3f808000,0xbf7b3e48,0x3f808000,0xbf7b3e48,0x3f2cbf3e,0xbf043f5c,0xbf2c3f3e,0x3f04bf5c,0xbdc9bf7f,0x3e953f75,0xbdc9bf7f,0x3e953f75,0xbf4ebf18,0x3f673edb,0x3f4e3f18,0xbf67bedb,
0x3f80,0x3e483f7b,0x3f80,0x3e483f7b,0x3f80bd49,0x3f78be79,0xbf803d49,0xbf783e79,0xbdc9bf7f,0xbe95bf75,0xbdc9bf7f,0xbe95bf75,0xbf7d3e16,0xbf713eac,0x3f7dbe16,0x3f71beac,
0x3f808000,0x3f7bbe48,0x3f808000,0x3f7bbe48,0xbd49bf80,0xbe79bf78,0x3d493f80,0x3e793f78,0xbf7f3dc9,0xbf753e95,0xbf7f3dc9,0xbf753e95,0x3e163f7d,0x3eac3f71,0xbe16bf7d,0xbeacbf71,
0x3f80,0xbe48bf7b,0x3f80,0xbe48bf7b,0x3f2cbf3e,0xbf043f5c,0xbf2c3f3e,0x3f04bf5c,0xbf7f3dc9,0x3f75be95,0xbf7f3dc9,0x3f75be95,0x3f4e3f18,0xbf67bedb,0xbf4ebf18,0x3f673edb,
0x3f808000,0xbf7b3e48,0x3f808000,0xbf7b3e48,0xbf3ebf2c,0x3f5c3f04,0x3f3e3f2c,0xbf5cbf04,0x3dc93f7f,0xbe95bf75,0x3dc93f7f,0xbe95bf75,0x3f18bf4e,0xbedb3f67,0xbf183f4e,0x3edbbf67,
0x80003600,0x80003600,0xb4c835fb,0xb4c835fb,0x80003600,0x80003600,0x34c8b5fb,0x34c8b5fb,0x80003600,0x80003600,0xb4c835fb,0xb4c835fb,0x80003600,0x80003600,0x34c8b5fb,0x34c8b5fb,
0x36000000,0x36000000,0x35fb34c8,0x35fb34c8,0x36000000,0x36000000,0xb5fbb4c8,0xb5fbb4c8,0x36000000,0x36000000,0x35fb34c8,0x35fb34c8,0x36000000,0x36000000,0xb5fbb4c8,0xb5fbb4c8,
0xb3c93600,0x33c9b600,0xb4f935f8,0x34f9b5f8,0xb5be35ac,0x35beb5ac,0x35dcb584,0xb5dc3584,0xb600b3c9,0x360033c9,0xb5f8b4f9,0x35f834f9,0xb5acb5be,0x35ac35be,0x358435dc,0xb584b5dc,
0x360033c9,0xb600b3c9,0x35f834f9,0xb5f8b4f9,0x35ac35be,0xb5acb5be,0xb584b5dc,0x358435dc,0xb3c93600,0x33c9b600,0xb4f935f8,0x34f9b5f8,0xb5be35ac,0x35beb5ac,0x35dcb584,0xb5dc3584,
0xb44935ff,0xb44935ff,0xb51535f5,0xb51535f5,0xb5ffb449,0xb5ffb449,0x35f53515,0x35f53515,0x3449b5ff,0x3449b5ff,0x3515b5f5,0x3515b5f5,0x35ff3449,0x35ff3449,0xb5f5b515,0xb5f5b515,
0x35ff3449,0x35ff3449,0x35f53515,0x35f53515,0xb44935ff,0xb44935ff,0x3515b5f5,0x3515b5f5,0xb5ffb449,0xb5ffb449,0xb5f5b515,0xb5f5b515,0x3449b5ff,0x3449b5ff,0xb51535f5,0xb51535f5,
0xb49635fd,0x3496b5fd,0xb52c35f1,0x352cb5f1,0xb598b5ce,0x359835ce,0x355b35e7,0xb55bb5e7,0x35fd3496,0xb5fdb496,0x35f1352c,0xb5f1b52c,0xb5ce3598,0x35ceb598,0x35e7b55b,0xb5e7355b,
0x35fd3496,0xb5fdb496,0x35f1352c,0xb5f1b52c,0xb5ce3598,0x35ceb598,0x35e7b55b,0xb5e7355b,0x3496b5fd,0xb49635fd,0x352cb5f1,0xb52c35f1,0x359835ce,0xb598b5ce,0xb55bb5e7,0x355b35e7,
0x3f80,0x3ec43f6d,0x3f80,0x3ec43f6d,0x3dc93f7f,0x3ef13f62,0xbdc9bf7f,0xbef1bf62,0x3e483f7b,0x3f0e3f55,0x3e483f7b,0x3f0e3f55,0x3e953f75,0x3f223f46,0xbe95bf75,0xbf22bf46,
0x3f808000,0x3f6dbec4,0x3f808000,0x3f6dbec4,0x3f7fbdc9,0x3f62bef1,0xbf7f3dc9,0xbf623ef1,0x3f7bbe48,0x3f55bf0e,0x3f7bbe48,0x3f55bf0e,0x3f75be95,0x3f46bf22,0xbf753e95,0xbf463f22,
0x3f80,0xbec4bf6d,0x3f80,0xbec4bf6d,0x3f463f22,0xbf75be95,0xbf46bf22,0x3f753e95,0x3f7bbe48,0xbf553f0e,0x3f7bbe48,0xbf553f0e,0x3ef1bf62,0xbdc93f7f,0xbef13f62,0x3dc9bf7f,
0x3f808000,0xbf6d3ec4,0x3f808000,0xbf6d3ec4,0x3f22bf46,0xbe953f75,0xbf223f46,0x3e95bf75,0xbe48bf7b,0x3f0e3f55,0xbe48bf7b,0x3f0e3f55,0xbf62bef1,0x3f7f3dc9,0x3f623ef1,0xbf7fbdc9,
0x3f80,0x3ec43f6d,0x3f80,0x3ec43f6d,0x3f7fbdc9,0x3f62bef1,0xbf7f3dc9,0xbf623ef1,0xbe48bf7b,0xbf0ebf55,0xbe48bf7b,0xbf0ebf55,0xbf753e95,0xbf463f22,0x3f75be95,0x3f46bf22,
0x3f808000,0x3f6dbec4,0x3f808000,0x3f6dbec4,0xbdc9bf7f,0xbef1bf62,0x3dc93f7f,0x3ef13f62,0xbf7b3e48,0xbf553f0e,0xbf7b3e48,0xbf553f0e,0x3e953f75,0x3f223f46,0xbe95bf75,0xbf22bf46,
0x3f80,0xbec4bf6d,0x3f80,0xbec4bf6d,0x3f22bf46,0xbe953f75,0xbf223f46,0x3e95bf75,0xbf7b3e48,0x3f55bf0e,0xbf7b3e48,0x3f55bf0e,0x3f623ef1,0xbf7fbdc9,0xbf62bef1,0x3f7f3dc9,
0x3f808000,0xbf6d3ec4,0x3f808000,0xbf6d3ec4,0xbf46bf22,0x3f753e95,0x3f463f22,0xbf75be95,0x3e483f7b,0xbf0ebf55,0x3e483f7b,0xbf0ebf55,0x3ef1bf62,0xbdc93f7f,0xbef13f62,0x3dc9bf7f,
0x80003600,0x80003600,0xb54435ed,0xb54435ed,0x80003600,0x80003600,0x3544b5ed,0x3544b5ed,0x80003600,0x80003600,0xb54435ed,0xb54435ed,0x80003600,0x80003600,0x3544b5ed,0x3544b5ed,
0x36000000,0x36000000,0x35ed3544,0x35ed3544,0x36000000,0x36000000,0xb5edb544,0xb5edb544,0x36000000,0x36000000,0x35ed3544,0x35ed3544,0x36000000,0x36000000,0xb5edb544,0xb5edb544,
0xb44935ff,0x3449b5ff,0xb57135e2,0x3571b5e2,0xb5c635a2,0x35c6b5a2,0x35f5b515,0xb5f53515,0xb5ffb449,0x35ff3449,0xb5e2b571,0x35e23571,0xb5a2b5c6,0x35a235c6,0x351535f5,0xb515b5f5,
0x35ff3449,0xb5ffb449,0x35e23571,0xb5e2b571,0x35a235c6,0xb5a2b5c6,0xb515b5f5,0x351535f5,0xb44935ff,0x3449b5ff,0xb57135e2,0x3571b5e2,0xb5c635a2,0x35c6b5a2,0x35f5b515,0xb5f53515,
0xb4c835fb,0xb4c835fb,0xb58e35d5,0xb58e35d5,0xb5fbb4c8,0xb5fbb4c8,0x35d5358e,0x35d5358e,0x34c8b5fb,0x34c8b5fb,0x358eb5d5,0x358eb5d5,0x35fb34c8,0x35fb34c8,0xb5d5b58e,0xb5d5b58e,
0x35fb34c8,0x35fb34c8,0x35d5358e,0x35d5358e,0xb4c835fb,0xb4c835fb,0x358eb5d5,0x358eb5d5,0xb5fbb4c8,0xb5fbb4c8,0xb5d5b58e,0xb5d5b58e,0x34c8b5fb,0x34c8b5fb,0xb58e35d5,0xb58e35d5,
0xb51535f5,0x3515b5f5,0xb5a235c6,0x35a2b5c6,0xb571b5e2,0x357135e2,0x344935ff,0xb449b5ff,0x35f53515,0xb5f5b515,0x35c635a2,0xb5c6b5a2,0xb5e23571,0x35e2b571,0x35ffb449,0xb5ff3449,
0x35f53515,0xb5f5b515,0x35c635a2,0xb5c6b5a2,0xb5e23571,0x35e2b571,0x35ffb449,0xb5ff3449,0x3515b5f5,0xb51535f5,0x35a2b5c6,0xb5a235c6,0x357135e2,0xb571b5e2,0xb449b5ff,0x344935ff,
0x3f80,0x3f0e3f55,0x3f80,0x3f0e3f55,0x3e163f7d,0x3f2c3f3e,0xbe16bf7d,0xbf2cbf3e,0x3e953f75,0x3f463f22,0x3e953f75,0x3f463f22,0x3edb3f67,0x3f5c3f04,0xbedbbf67,0xbf5cbf04,
0x3f808000,0x3f55bf0e,0x3f808000,0x3f55bf0e,0x3f7dbe16,0x3f3ebf2c,0xbf7d3e16,0xbf3e3f2c,0x3f75be95,0x3f22bf46,0x3f75be95,0x3f22bf46,0x3f67bedb,0x3f04bf5c,0xbf673edb,0xbf043f5c,
0x3f80,0xbf0ebf55,0x3f80,0xbf0ebf55,0x3f4e3f18,0xbf80bd49,0xbf4ebf18,0x3f803d49,0x3f75be95,0xbf223f46,0x3f75be95,0xbf223f46,0x3eacbf71,0x3e793f78,0xbeac3f71,0xbe79bf78,
0x3f808000,0xbf553f0e,0x3f808000,0xbf553f0e,0x3f18bf4e,0xbd493f80,0xbf183f4e,0x3d49bf80,0xbe95bf75,0x3f463f22,0xbe95bf75,0x3f463f22,0xbf71beac,0x3f78be79,0x3f713eac,0xbf783e79,
0x3f80,0x3f0e3f55,0x3f80,0x3f0e3f55,0x3f7dbe16,0x3f3ebf2c,0xbf7d3e16,0xbf3e3f2c,0xbe95bf75,0xbf46bf22,0xbe95bf75,0xbf46bf22,0xbf673edb,0xbf043f5c,0x3f67bedb,0x3f04bf5c,
0x3f808000,0x3f55bf0e,0x3f808000,0x3f55bf0e,0xbe16bf7d,0xbf2cbf3e,0x3e163f7d,0x3f2c3f3e,0xbf753e95,0xbf223f46,0xbf753e95,0xbf223f46,0x3edb3f67,0x3f5c3f04,0xbedbbf67,0xbf5cbf04,
0x3f80,0xbf0ebf55,0x3f80,0xbf0ebf55,0x3f18bf4e,0xbd493f80,0xbf183f4e,0x3d49bf80,0xbf753e95,0x3f22bf46,0xbf753e95,0x3f22bf46,0x3f713eac,0xbf783e79,0xbf71beac,0x3f78be79,
0x3f808000,0xbf553f0e,0x3f808000,0xbf553f0e,0xbf4ebf18,0x3f803d49,0x3f4e3f18,0xbf80bd49,0x3e953f75,0xbf46bf22,0x3e953f75,0xbf46bf22,0x3eacbf71,0x3e793f78,0xbeac3f71,0xbe79bf78,
0x80003600,0x80003600,0xb58e35d5,0xb58e35d5,0x80003600,0x80003600,0x358eb5d5,0x358eb5d5,0x80003600,0x80003600,0xb58e35d5,0xb58e35d5,0x80003600,0x80003600,0x358eb5d5,0x358eb5d5,
0x36000000,0x36000000,0x35d5358e,0x35d5358e,0x36000000,0x36000000,0xb5d5b58e,0xb5d5b58e,0x36000000,0x36000000,0x35d5358e,0x35d5358e,0x36000000,0x36000000,0xb5d5b58e,0xb5d5b58e,
0xb49635fd,0x3496b5fd,0xb5ac35be,0x35acb5be,0xb5ce3598,0x35ceb598,0x3600b3c9,0xb60033c9,0xb5fdb496,0x35fd3496,0xb5beb5ac,0x35be35ac,0xb598b5ce,0x359835ce,0x33c93600,0xb3c9b600,
0x35fd3496,0xb5fdb496,0x35be35ac,0xb5beb5ac,0x359835ce,0xb598b5ce,0xb3c9b600,0x33c93600,0xb49635fd,0x3496b5fd,0xb5ac35be,0x35acb5be,0xb5ce3598,0x35ceb598,0x3600b3c9,0xb60033c9,
0xb51535f5,0xb51535f5,0xb5c635a2,0xb5c635a2,0xb5f5b515,0xb5f5b515,0x35a235c6,0x35a235c6,0x3515b5f5,0x3515b5f5,0x35c6b5a2,0x35c6b5a2,0x35f53515,0x35f53515,0xb5a2b5c6,0xb5a2b5c6,
0x35f53515,0x35f53515,0x35a235c6,0x35a235c6,0xb51535f5,0xb51535f5,0x35c6b5a2,0x35c6b5a2,0xb5f5b515,0xb5f5b515,0xb5a2b5c6,0xb5a2b5c6,0x3515b5f5,0x3515b5f5,0xb5c635a2,0xb5c635a2,
0xb55b35e7,0x355bb5e7,0xb5dc3584,0x35dcb584,0xb52cb5f1,0x352c35f1,0xb4f935f8,0x34f9b5f8,0x35e7355b,0xb5e7b55b,0x358435dc,0xb584b5dc,0xb5f1352c,0x35f1b52c,0x35f834f9,0xb5f8b4f9,
0x35e7355b,0xb5e7b55b,0x358435dc,0xb584b5dc,0xb5f1352c,0x35f1b52c,0x35f834f9,0xb5f8b4f9,0x355bb5e7,0xb55b35e7,0x35dcb584,0xb5dc3584,0x352c35f1,0xb52cb5f1,0x34f9b5f8,0xb4f935f8,
0x3f80,0x3f353f35,0x3f80,0x3f353f35,0x3e483f7b,0x3f553f0e,0xbe48bf7b,0xbf55bf0e,0x3ec43f6d,0x3f6d3ec4,0x3ec43f6d,0x3f6d3ec4,0x3f0e3f55,0x3f7b3e48,0xbf0ebf55,0xbf7bbe48,
0x3f808000,0x3f35bf35,0x3f808000,0x3f35bf35,0x3f7bbe48,0x3f0ebf55,0xbf7b3e48,0xbf0e3f55,0x3f6dbec4,0x3ec4bf6d,0x3f6dbec4,0x3ec4bf6d,0x3f55bf0e,0x3e48bf7b,0xbf553f0e,0xbe483f7b,
0x3f80,0xbf35bf35,0x3f80,0xbf35bf35,0x3f553f0e,0xbf7b3e48,0xbf55bf0e,0x3f7bbe48,0x3f6dbec4,0xbec43f6d,0x3f6dbec4,0xbec43f6d,0x3e48bf7b,0x3f0e3f55,0xbe483f7b,0xbf0ebf55,
0x3f808000,0xbf353f35,0x3f808000,0xbf353f35,0x3f0ebf55,0x3e483f7b,0xbf0e3f55,0xbe48bf7b,0xbec4bf6d,0x3f6d3ec4,0xbec4bf6d,0x3f6d3ec4,0xbf7bbe48,0x3f55bf0e,0x3f7b3e48,0xbf553f0e,
0x3f80,0x3f353f35,0x3f80,0x3f353f35,0x3f7bbe48,0x3f0ebf55,0xbf7b3e48,0xbf0e3f55,0xbec4bf6d,0xbf6dbec4,0xbec4bf6d,0xbf6dbec4,0xbf553f0e,0xbe483f7b,0x3f55bf0e,0x3e48bf7b,
0x3f808000,0x3f35bf35,0x3f808000,0x3f35bf35,0xbe48bf7b,0xbf55bf0e,0x3e483f7b,0x3f553f0e,0xbf6d3ec4,0xbec43f6d,0xbf6d3ec4,0xbec43f6d,0x3f0e3f55,0x3f7b3e48,0xbf0ebf55,0xbf7bbe48,
0x3f80,0xbf35bf35,0x3f80,0xbf35bf35,0x3f0ebf55,0x3e483f7b,0xbf0e3f55,0xbe48bf7b,0xbf6d3ec4,0x3ec4bf6d,0xbf6d3ec4,0x3ec4bf6d,0x3f7b3e48,0xbf553f0e,0xbf7bbe48,0x3f55bf0e,
0x3f808000,0xbf353f35,0x3f808000,0xbf353f35,0xbf55bf0e,0x3f7bbe48,0x3f553f0e,0xbf7b3e48,0x3ec43f6d,0xbf6dbec4,0x3ec43f6d,0xbf6dbec4,0x3e48bf7b,0x3f0e3f55,0xbe483f7b,0xbf0ebf55,
0x80003600,0x80003600,0xb5b535b5,0xb5b535b5,0x80003600,0x80003600,0x35b5b5b5,0x35b5b5b5,0x80003600,0x80003600,0xb5b535b5,0xb5b535b5,0x80003600,0x80003600,0x35b5b5b5,0x35b5b5b5,
0x36000000,0x36000000,0x35b535b5,0x35b535b5,0x36000000,0x36000000,0xb5b5b5b5,0xb5b5b5b5,0x36000000,0x36000000,0x35b535b5,0x35b535b5,0x36000000,0x36000000,0xb5b5b5b5,0xb5b5b5b5,
0xb4c835fb,0x34c8b5fb,0xb5d5358e,0x35d5b58e,0xb5d5358e,0x35d5b58e,0x35fb34c8,0xb5fbb4c8,0xb5fbb4c8,0x35fb34c8,0xb58eb5d5,0x358e35d5,0xb58eb5d5,0x358e35d5,0xb4c835fb,0x34c8b5fb,
0x35fb34c8,0xb5fbb4c8,0x358e35d5,0xb58eb5d5,0x358e35d5,0xb58eb5d5,0x34c8b5fb,0xb4c835fb,0xb4c835fb,0x34c8b5fb,0xb5d5358e,0x35d5b58e,0xb5d5358e,0x35d5b58e,0x35fb34c8,0xb5fbb4c8,
0xb54435ed,0xb54435ed,0xb5ed3544,0xb5ed3544,0xb5edb544,0xb5edb544,0x354435ed,0x354435ed,0x3544b5ed,0x3544b5ed,0x35edb544,0x35edb544,0x35ed3544,0x35ed3544,0xb544b5ed,0xb544b5ed,
0x35ed3544,0x35ed3544,0x354435ed,0x354435ed,0xb54435ed,0xb54435ed,0x35edb544,0x35edb544,0xb5edb544,0xb5edb544,0xb544b5ed,0xb544b5ed,0x3544b5ed,0x3544b5ed,0xb5ed3544,0xb5ed3544,
0xb58e35d5,0x358eb5d5,0xb5fb34c8,0x35fbb4c8,0xb4c8b5fb,0x34c835fb,0xb58e35d5,0x358eb5d5,0x35d5358e,0xb5d5b58e,0x34c835fb,0xb4c8b5fb,0xb5fb34c8,0x35fbb4c8,0x35d5358e,0xb5d5b58e,
0x35d5358e,0xb5d5b58e,0x34c835fb,0xb4c8b5fb,0xb5fb34c8,0x35fbb4c8,0x35d5358e,0xb5d5b58e,0x358eb5d5,0xb58e35d5,0x35fbb4c8,0xb5fb34c8,0x34c835fb,0xb4c8b5fb,0x358eb5d5,0xb58e35d5,
0x3f80,0x3f553f0e,0x3f80,0x3f553f0e,0x3e793f78,0x3f713eac,0xbe79bf78,0xbf71beac,0x3ef13f62,0x3f7f3dc9,0x3ef13f62,0x3f7f3dc9,0x3f2c3f3e,0x3f7dbe16,0xbf2cbf3e,0xbf7d3e16,
0x3f808000,0x3f0ebf55,0x3f808000,0x3f0ebf55,0x3f78be79,0x3eacbf71,0xbf783e79,0xbeac3f71,0x3f62bef1,0x3dc9bf7f,0x3f62bef1,0x3dc9bf7f,0x3f3ebf2c,0xbe16bf7d,0xbf3e3f2c,0x3e163f7d,
0x3f80,0xbf55bf0e,0x3f80,0xbf55bf0e,0x3f5c3f04,0xbf673edb,0xbf5cbf04,0x3f67bedb,0x3f62bef1,0xbdc93f7f,0x3f62bef1,0xbdc93f7f,0x3d49bf80,0x3f4e3f18,0xbd493f80,0xbf4ebf18,
0x3f808000,0xbf0e3f55,0x3f808000,0xbf0e3f55,0x3f04bf5c,0x3edb3f67,0xbf043f5c,0xbedbbf67,0xbef1bf62,0x3f7f3dc9,0xbef1bf62,0x3f7f3dc9,0xbf80bd49,0x3f18bf4e,0x3f803d49,0xbf183f4e,
0x3f80,0x3f553f0e,0x3f80,0x3f553f0e,0x3f78be79,0x3eacbf71,0xbf783e79,0xbeac3f71,0xbef1bf62,0xbf7fbdc9,0xbef1bf62,0xbf7fbdc9,0xbf3e3f2c,0x3e163f7d,0x3f3ebf2c,0xbe16bf7d,
0x3f808000,0x3f0ebf55,0x3f808000,0x3f0ebf55,0xbe79bf78,0xbf71beac,0x3e793f78,0x3f713eac,0xbf623ef1,0xbdc93f7f,0xbf623ef1,0xbdc93f7f,0x3f2c3f3e,0x3f7dbe16,0xbf2cbf3e,0xbf7d3e16,
0x3f80,0xbf55bf0e,0x3f80,0xbf55bf0e,0x3f04bf5c,0x3edb3f67,0xbf043f5c,0xbedbbf67,0xbf623ef1,0x3dc9bf7f,0xbf623ef1,0x3dc9bf7f,0x3f803d49,0xbf183f4e,0xbf80bd49,0x3f18bf4e,
0x3f808000,0xbf0e3f55,0x3f808000,0xbf0e3f55,0xbf5cbf04,0x3f67bedb,0x3f5c3f04,0xbf673edb,0x3ef13f62,0xbf7fbdc9,0x3ef13f62,0xbf7fbdc9,0x3d49bf80,0x3f4e3f18,0xbd493f80,0xbf4ebf18,
0x80003600,0x80003600,0xb5d5358e,0xb5d5358e,0x80003600,0x80003600,0x35d5b58e,0x35d5b58e,0x80003600,0x80003600,0xb5d5358e,0xb5d5358e,0x80003600,0x80003600,0x35d5b58e,0x35d5b58e,
0x36000000,0x36000000,0x358e35d5,0x358e35d5,0x36000000,0x36000000,0xb58eb5d5,0xb58eb5d5,0x36000000,0x36000000,0x358e35d5,0x358e35d5,0x36000000,0x36000000,0xb58eb5d5,0xb58eb5d5,
0xb4f935f8,0x34f9b5f8,0xb5f1352c,0x35f1b52c,0xb5dc3584,0x35dcb584,0x35e7355b,0xb5e7b55b,0xb5f8b4f9,0x35f834f9,0xb52cb5f1,0x352c35f1,0xb584b5dc,0x358435dc,0xb55b35e7,0x355bb5e7,
0x35f834f9,0xb5f8b4f9,0x352c35f1,0xb52cb5f1,0x358435dc,0xb584b5dc,0x355bb5e7,0xb55b35e7,0xb4f935f8,0x34f9b5f8,0xb5f1352c,0x35f1b52c,0xb5dc3584,0x35dcb584,0x35e7355b,0xb5e7b55b,
0xb57135e2,0xb57135e2,0xb5ff3449,0xb5ff3449,0xb5e2b571,0xb5e2b571,0x344935ff,0x344935ff,0x3571b5e2,0x3571b5e2,0x35ffb449,0x35ffb449,0x35e23571,0x35e23571,0xb449b5ff,0xb449b5ff,
0x35e23571,0x35e23571,0x344935ff,0x344935ff,0xb57135e2,0xb57135e2,0x35ffb449,0x35ffb449,0xb5e2b571,0xb5e2b571,0xb449b5ff,0xb449b5ff,0x3571b5e2,0x3571b5e2,0xb5ff3449,0xb5ff3449,
0xb5ac35be,0x35acb5be,0xb5fdb496,0x35fd3496,0xb3c9b600,0x33c93600,0xb5ce3598,0x35ceb598,0x35be35ac,0xb5beb5ac,0xb49635fd,0x3496b5fd,0xb60033c9,0x3600b3c9,0x359835ce,0xb598b5ce,
0x35be35ac,0xb5beb5ac,0xb49635fd,0x3496b5fd,0xb60033c9,0x3600b3c9,0x359835ce,0xb598b5ce,0x35acb5be,0xb5ac35be,0x35fd3496,0xb5fdb496,0x33c93600,0xb3c9b600,0x35ceb598,0xb5ce3598,
0x3f80,0x3f6d3ec4,0x3f80,0x3f6d3ec4,0x3e953f75,0x3f7f3dc9,0xbe95bf75,0xbf7fbdc9,0x3f0e3f55,0x3f7bbe48,0x3f0e3f55,0x3f7bbe48,0x3f463f22,0x3f62bef1,0xbf46bf22,0xbf623ef1,
0x3f808000,0x3ec4bf6d,0x3f808000,0x3ec4bf6d,0x3f75be95,0x3dc9bf7f,0xbf753e95,0xbdc93f7f,0x3f55bf0e,0xbe48bf7b,0x3f55bf0e,0xbe48bf7b,0x3f22bf46,0xbef1bf62,0xbf223f46,0x3ef13f62,
0x3f80,0xbf6dbec4,0x3f80,0xbf6dbec4,0x3f623ef1,0xbf463f22,0xbf62bef1,0x3f46bf22,0x3f55bf0e,0x3e483f7b,0x3f55bf0e,0x3e483f7b,0xbdc9bf7f,0x3f753e95,0x3dc93f7f,0xbf75be95,
0x3f808000,0xbec43f6d,0x3f808000,0xbec43f6d,0x3ef1bf62,0x3f223f46,0xbef13f62,0xbf22bf46,0xbf0ebf55,0x3f7bbe48,0xbf0ebf55,0x3f7bbe48,0xbf7f3dc9,0x3e95bf75,0x3f7fbdc9,0xbe953f75,
0x3f80,0x3f6d3ec4,0x3f80,0x3f6d3ec4,0x3f75be95,0x3dc9bf7f,0xbf753e95,0xbdc93f7f,0xbf0ebf55,0xbf7b3e48,0xbf0ebf55,0xbf7b3e48,0xbf223f46,0x3ef13f62,0x3f22bf46,0xbef1bf62,
0x3f808000,0x3ec4bf6d,0x3f808000,0x3ec4bf6d,0xbe95bf75,0xbf7fbdc9,0x3e953f75,0x3f7f3dc9,0xbf553f0e,0x3e483f7b,0xbf553f0e,0x3e483f7b,0x3f463f22,0x3f62bef1,0xbf46bf22,0xbf623ef1,
0x3f80,0xbf6dbec4,0x3f80,0xbf6dbec4,0x3ef1bf62,0x3f223f46,0xbef13f62,0xbf22bf46,0xbf553f0e,0xbe48bf7b,0xbf553f0e,0xbe48bf7b,0x3f7fbdc9,0xbe953f75,0xbf7f3dc9,0x3e95bf75,
0x3f808000,0xbec43f6d,0x3f808000,0xbec43f6d,0xbf62bef1,0x3f46bf22,0x3f623ef1,0xbf463f22,0x3f0e3f55,0xbf7b3e48,0x3f0e3f55,0xbf7b3e48,0xbdc9bf7f,0x3f753e95,0x3dc93f7f,0xbf75be95,
0x80003600,0x80003600,0xb5ed3544,0xb5ed3544,0x80003600,0x80003600,0x35edb544,0x35edb544,0x80003600,0x80003600,0xb5ed3544,0xb5ed3544,0x80003600,0x80003600,0x35edb544,0x35edb544,
0x36000000,0x36000000,0x354435ed,0x354435ed,0x36000000,0x36000000,0xb544b5ed,0xb544b5ed,0x36000000,0x36000000,0x354435ed,0x354435ed,0x36000000,0x36000000,0xb544b5ed,0xb544b5ed,
0xb51535f5,0x3515b5f5,0xb5ff3449,0x35ffb449,0xb5e23571,0x35e2b571,0x35c635a2,0xb5c6b5a2,0xb5f5b515,0x35f53515,0xb449b5ff,0x344935ff,0xb571b5e2,0x357135e2,0xb5a235c6,0x35a2b5c6,
0x35f53515,0xb5f5b515,0x344935ff,0xb449b5ff,0x357135e2,0xb571b5e2,0x35a2b5c6,0xb5a235c6,0xb51535f5,0x3515b5f5,0xb5ff3449,0x35ffb449,0xb5e23571,0x35e2b571,0x35c635a2,0xb5c6b5a2,
0xb58e35d5,0xb58e35d5,0xb5fbb4c8,0xb5fbb4c8,0xb5d5b58e,0xb5d5b58e,0xb4c835fb,0xb4c835fb,0x358eb5d5,0x358eb5d5,0x35fb34c8,0x35fb34c8,0x35d5358e,0x35d5358e,0x34c8b5fb,0x34c8b5fb,
0x35d5358e,0x35d5358e,0xb4c835fb,0xb4c835fb,0xb58e35d5,0xb58e35d5,0x35fb34c8,0x35fb34c8,0xb5d5b58e,0xb5d5b58e,0x34c8b5fb,0x34c8b5fb,0x358eb5d5,0x358eb5d5,0xb5fbb4c8,0xb5fbb4c8,
0xb5c635a2,0x35c6b5a2,0xb5e2b571,0x35e23571,0x3449b5ff,0xb44935ff,0xb5f53515,0x35f5b515,0x35a235c6,0xb5a2b5c6,0xb57135e2,0x3571b5e2,0xb5ffb449,0x35ff3449,0x351535f5,0xb515b5f5,
0x35a235c6,0xb5a2b5c6,0xb57135e2,0x3571b5e2,0xb5ffb449,0x35ff3449,0x351535f5,0xb515b5f5,0x35c6b5a2,0xb5c635a2,0x35e23571,0xb5e2b571,0xb44935ff,0x3449b5ff,0x35f5b515,0xb5f53515,
0x3f80,0x3f7b3e48,0x3f80,0x3f7b3e48,0x3eac3f71,0x3f7dbe16,0xbeacbf71,0xbf7d3e16,0x3f223f46,0x3f62bef1,0x3f223f46,0x3f62bef1,0x3f5c3f04,0x3f2cbf3e,0xbf5cbf04,0xbf2c3f3e,
0x3f808000,0x3e48bf7b,0x3f808000,0x3e48bf7b,0x3f71beac,0xbe16bf7d,0xbf713eac,0x3e163f7d,0x3f46bf22,0xbef1bf62,0x3f46bf22,0xbef1bf62,0x3f04bf5c,0xbf3ebf2c,0xbf043f5c,0x3f3e3f2c,
0x3f80,0xbf7bbe48,0x3f80,0xbf7bbe48,0x3f673edb,0xbf183f4e,0xbf67bedb,0x3f18bf4e,0x3f46bf22,0x3ef13f62,0x3f46bf22,0x3ef13f62,0xbe79bf78,0x3f80bd49,0x3e793f78,0xbf803d49,
0x3f808000,0xbe483f7b,0x3f808000,0xbe483f7b,0x3edbbf67,0x3f4e3f18,0xbedb3f67,0xbf4ebf18,0xbf22bf46,0x3f62bef1,0xbf22bf46,0x3f62bef1,0xbf783e79,0xbd49bf80,0x3f78be79,0x3d493f80,
0x3f80,0x3f7b3e48,0x3f80,0x3f7b3e48,0x3f71beac,0xbe16bf7d,0xbf713eac,0x3e163f7d,0xbf22bf46,0xbf623ef1,0xbf22bf46,0xbf623ef1,0xbf043f5c,0x3f3e3f2c,0x3f04bf5c,0xbf3ebf2c,
0x3f808000,0x3e48bf7b,0x3f808000,0x3e48bf7b,0xbeacbf71,0xbf7d3e16,0x3eac3f71,0x3f7dbe16,0xbf463f22,0x3ef13f62,0xbf463f22,0x3ef13f62,0x3f5c3f04,0x3f2cbf3e,0xbf5cbf04,0xbf2c3f3e,
0x3f80,0xbf7bbe48,0x3f80,0xbf7bbe48,0x3edbbf67,0x3f4e3f18,0xbedb3f67,0xbf4ebf18,0xbf463f22,0xbef1bf62,0xbf463f22,0xbef1bf62,0x3f78be79,0x3d493f80,0xbf783e79,0xbd49bf80,
0x3f808000,0xbe483f7b,0x3f808000,0xbe483f7b,0xbf67bedb,0x3f18bf4e,0x3f673edb,0xbf183f4e,0x3f223f46,0xbf623ef1,0x3f223f46,0xbf623ef1,0xbe79bf78,0x3f80bd49,0x3e793f78,0xbf803d49,
0x80003600,0x80003600,0xb5fb34c8,0xb5fb34c8,0x80003600,0x80003600,0x35fbb4c8,0x35fbb4c8,0x80003600,0x80003600,0xb5fb34c8,0xb5fb34c8,0x80003600,0x80003600,0x35fbb4c8,0x35fbb4c8,
0x36000000,0x36000000,0x34c835fb,0x34c835fb,0x36000000,0x36000000,0xb4c8b5fb,0xb4c8b5fb,0x36000000,0x36000000,0x34c835fb,0x34c835fb,0x36000000,0x36000000,0xb4c8b5fb,0xb4c8b5fb,
0xb52c35f1,0x352cb5f1,0xb5fdb496,0x35fd3496,0xb5e7355b,0x35e7b55b,0x359835ce,0xb598b5ce,0xb5f1b52c,0x35f1352c,0x3496b5fd,0xb49635fd,0xb55bb5e7,0x355b35e7,0xb5ce3598,0x35ceb598,
0x35f1352c,0xb5f1b52c,0xb49635fd,0x3496b5fd,0x355b35e7,0xb55bb5e7,0x35ceb598,0xb5ce3598,0xb52c35f1,0x352cb5f1,0xb5fdb496,0x35fd3496,0xb5e7355b,0x35e7b55b,0x359835ce,0xb598b5ce,
0xb5a235c6,0xb5a235c6,0xb5e2b571,0xb5e2b571,0xb5c6b5a2,0xb5c6b5a2,0xb57135e2,0xb57135e2,0x35a2b5c6,0x35a2b5c6,0x35e23571,0x35e23571,0x35c635a2,0x35c635a2,0x3571b5e2,0x3571b5e2,
0x35c635a2,0x35c635a2,0xb57135e2,0xb57135e2,0xb5a235c6,0xb5a235c6,0x35e23571,0x35e23571,0xb5c6b5a2,0xb5c6b5a2,0x3571b5e2,0x3571b5e2,0x35a2b5c6,0x35a2b5c6,0xb5e2b571,0xb5e2b571,
0xb5dc3584,0x35dcb584,0xb5acb5be,0x35ac35be,0x34f9b5f8,0xb4f935f8,0xb600b3c9,0x360033c9,0x358435dc,0xb584b5dc,0xb5be35ac,0x35beb5ac,0xb5f8b4f9,0x35f834f9,0xb3c93600,0x33c9b600,
0x358435dc,0xb584b5dc,0xb5be35ac,0x35beb5ac,0xb5f8b4f9,0x35f834f9,0xb3c93600,0x33c9b600,0x35dcb584,0xb5dc3584,0x35ac35be,0xb5acb5be,0xb4f935f8,0x34f9b5f8,0x360033c9,0xb600b3c9,
0x3f80,0x3f800000,0x3f80,0x3f800000,0x3ec43f6d,0x3f6dbec4,0xbec4bf6d,0xbf6d3ec4,0x3f353f35,0x3f35bf35,0x3f353f35,0x3f35bf35,0x3f6d3ec4,0x3ec4bf6d,0xbf6dbec4,0xbec43f6d,
0x3f808000,0xbf80,0x3f808000,0xbf80,0x3f6dbec4,0xbec4bf6d,0xbf6d3ec4,0x3ec43f6d,0x3f35bf35,0xbf35bf35,0x3f35bf35,0xbf35bf35,0x3ec4bf6d,0xbf6dbec4,0xbec43f6d,0x3f6d3ec4,
0x3f80,0xbf800000,0x3f80,0xbf800000,0x3f6d3ec4,0xbec43f6d,0xbf6dbec4,0x3ec4bf6d,0x3f35bf35,0x3f353f35,0x3f35bf35,0x3f353f35,0xbec4bf6d,0x3f6dbec4,0x3ec43f6d,0xbf6d3ec4,
0x3f808000,0x3f80,0x3f808000,0x3f80,0x3ec4bf6d,0x3f6d3ec4,0xbec43f6d,0xbf6dbec4,0xbf35bf35,0x3f35bf35,0xbf35bf35,0x3f35bf35,0xbf6d3ec4,0xbec4bf6d,0x3f6dbec4,0x3ec43f6d,
0x3f80,0x3f800000,0x3f80,0x3f800000,0x3f6dbec4,0xbec4bf6d,0xbf6d3ec4,0x3ec43f6d,0xbf35bf35,0xbf353f35,0xbf35bf35,0xbf353f35,0xbec43f6d,0x3f6d3ec4,0x3ec4bf6d,0xbf6dbec4,
0x3f808000,0xbf80,0x3f808000,0xbf80,0xbec4bf6d,0xbf6d3ec4,0x3ec43f6d,0x3f6dbec4,0xbf353f35,0x3f353f35,0xbf353f35,0x3f353f35,0x3f6d3ec4,0x3ec4bf6d,0xbf6dbec4,0xbec43f6d,
0x3f80,0xbf800000,0x3f80,0xbf800000,0x3ec4bf6d,0x3f6d3ec4,0xbec43f6d,0xbf6dbec4,0xbf353f35,0xbf35bf35,0xbf353f35,0xbf35bf35,0x3f6dbec4,0x3ec43f6d,0xbf6d3ec4,0xbec4bf6d,
0x3f808000,0x3f80,0x3f808000,0x3f80,0xbf6dbec4,0x3ec4bf6d,0x3f6d3ec4,0xbec43f6d,0x3f353f35,0xbf353f35,0x3f353f35,0xbf353f35,0xbec4bf6d,0x3f6dbec4,0x3ec43f6d,0xbf6d3ec4,
0x80003600,0x80003600,0xb6000000,0xb6000000,0x80003600,0x80003600,0x36000000,0x36000000,0x80003600,0x80003600,0xb6000000,0xb6000000,0x80003600,0x80003600,0x36000000,0x36000000,
0x36000000,0x36000000,0x3600,0x3600,0x36000000,0x36000000,0xb600,0xb600,0x36000000,0x36000000,0x3600,0x3600,0x36000000,0x36000000,0xb600,0xb600,
0xb54435ed,0x3544b5ed,0xb5edb544,0x35ed3544,0xb5ed3544,0x35edb544,0x354435ed,0xb544b5ed,0xb5edb544,0x35ed3544,0x3544b5ed,0xb54435ed,0xb544b5ed,0x354435ed,0xb5ed3544,0x35edb544,
0x35ed3544,0xb5edb544,0xb54435ed,0x3544b5ed,0x354435ed,0xb544b5ed,0x35edb544,0xb5ed3544,0xb54435ed,0x3544b5ed,0xb5edb544,0x35ed3544,0xb5ed3544,0x35edb544,0x354435ed,0xb544b5ed,
0xb5b535b5,0xb5b535b5,0xb5b5b5b5,0xb5b5b5b5,0xb5b5b5b5,0xb5b5b5b5,0xb5b535b5,0xb5b535b5,0x35b5b5b5,0x35b5b5b5,0x35b535b5,0x35b535b5,0x35b535b5,0x35b535b5,0x35b5b5b5,0x35b5b5b5,
0x35b535b5,0x35b535b5,0xb5b535b5,0xb5b535b5,0xb5b535b5,0xb5b535b5,0x35b535b5,0x35b535b5,0xb5b5b5b5,0xb5b5b5b5,0x35b5b5b5,0x35b5b5b5,0x35b5b5b5,0x35b5b5b5,0xb5b5b5b5,0xb5b5b5b5,
0xb5ed3544,0x35edb544,0xb544b5ed,0x354435ed,0x3544b5ed,0xb54435ed,0xb5edb544,0x35ed3544,0x354435ed,0xb544b5ed,0xb5ed3544,0x35edb544,0xb5edb544,0x35ed3544,0xb54435ed,0x3544b5ed,
0x354435ed,0xb544b5ed,0xb5ed3544,0x35edb544,0xb5edb544,0x35ed3544,0xb54435ed,0x3544b5ed,0x35edb544,0xb5ed3544,0x354435ed,0xb544b5ed,0xb54435ed,0x3544b5ed,0x35ed3544,0xb5edb544,
0x3f80,0x3f7bbe48,0x3f80,0x3f7bbe48,0x3edb3f67,0x3f4ebf18,0xbedbbf67,0xbf4e3f18,0x3f463f22,0x3ef1bf62,0x3f463f22,0x3ef1bf62,0x3f783e79,0x3d49bf80,0xbf78be79,0xbd493f80,
0x3f808000,0xbe48bf7b,0x3f808000,0xbe48bf7b,0x3f67bedb,0xbf18bf4e,0xbf673edb,0x3f183f4e,0x3f22bf46,0xbf62bef1,0x3f22bf46,0xbf62bef1,0x3e79bf78,0xbf80bd49,0xbe793f78,0x3f803d49,
0x3f80,0xbf7b3e48,0x3f80,0xbf7b3e48,0x3f713eac,0xbe163f7d,0xbf71beac,0x3e16bf7d,0x3f22bf46,0x3f623ef1,0x3f22bf46,0x3f623ef1,0xbf04bf5c,0x3f3ebf2c,0x3f043f5c,0xbf3e3f2c,
0x3f808000,0x3e483f7b,0x3f808000,0x3e483f7b,0x3eacbf71,0x3f7d3e16,0xbeac3f71,0xbf7dbe16,0xbf46bf22,0x3ef1bf62,0xbf46bf22,0x3ef1bf62,0xbf5c3f04,0xbf2cbf3e,0x3f5cbf04,0x3f2c3f3e,
0x3f80,0x3f7bbe48,0x3f80,0x3f7bbe48,0x3f67bedb,0xbf18bf4e,0xbf673edb,0x3f183f4e,0xbf46bf22,0xbef13f62,0xbf46bf22,0xbef13f62,0xbe793f78,0x3f803d49,0x3e79bf78,0xbf80bd49,
0x3f808000,0xbe48bf7b,0x3f808000,0xbe48bf7b,0xbedbbf67,0xbf4e3f18,0x3edb3f67,0x3f4ebf18,0xbf223f46,0x3f623ef1,0xbf223f46,0x3f623ef1,0x3f783e79,0x3d49bf80,0xbf78be79,0xbd493f80,
0x3f80,0xbf7b3e48,0x3f80,0xbf7b3e48,0x3eacbf71,0x3f7d3e16,0xbeac3f71,0xbf7dbe16,0xbf223f46,0xbf62bef1,0xbf223f46,0xbf62bef1,0x3f5cbf04,0x3f2c3f3e,0xbf5c3f04,0xbf2cbf3e,
0x3f808000,0x3e483f7b,0x3f808000,0x3e483f7b,0xbf71beac,0x3e16bf7d,0x3f713eac,0xbe163f7d,0x3f463f22,0xbef13f62,0x3f463f22,0xbef13f62,0xbf04bf5c,0x3f3ebf2c,0x3f043f5c,0xbf3e3f2c,
0x80003600,0x80003600,0xb5fbb4c8,0xb5fbb4c8,0x80003600,0x80003600,0x35fb34c8,0x35fb34c8,0x80003600,0x80003600,0xb5fbb4c8,0xb5fbb4c8,0x80003600,0x80003600,0x35fb34c8,0x35fb34c8,
0x36000000,0x36000000,0xb4c835fb,0xb4c835fb,0x36000000,0x36000000,0x34c8b5fb,0x34c8b5fb,0x36000000,0x36000000,0xb4c835fb,0xb4c835fb,0x36000000,0x36000000,0x34c8b5fb,0x34c8b5fb,
0xb55b35e7,0x355bb5e7,0xb5ceb598,0x35ce3598,0xb5f1352c,0x35f1b52c,0x349635fd,0xb496b5fd,0xb5e7b55b,0x35e7355b,0x3598b5ce,0xb59835ce,0xb52cb5f1,0x352c35f1,0xb5fd3496,0x35fdb496,
0x35e7355b,0xb5e7b55b,0xb59835ce,0x3598b5ce,0x352c35f1,0xb52cb5f1,0x35fdb496,0xb5fd3496,0xb55b35e7,0x355bb5e7,0xb5ceb598,0x35ce3598,0xb5f1352c,0x35f1b52c,0x349635fd,0xb496b5fd,
0xb5c635a2,0xb5c635a2,0xb571b5e2,0xb571b5e2,0xb5a2b5c6,0xb5a2b5c6,0xb5e23571,0xb5e23571,0x35c6b5a2,0x35c6b5a2,0x357135e2,0x357135e2,0x35a235c6,0x35a235c6,0x35e2b571,0x35e2b571,
0x35a235c6,0x35a235c6,0xb5e23571,0xb5e23571,0xb5c635a2,0xb5c635a2,0x357135e2,0x357135e2,0xb5a2b5c6,0xb5a2b5c6,0x35e2b571,0x35e2b571,0x35c6b5a2,0x35c6b5a2,0xb571b5e2,0xb571b5e2,
0xb5f834f9,0x35f8b4f9,0xb3c9b600,0x33c93600,0x3584b5dc,0xb58435dc,0xb5beb5ac,0x35be35ac,0x34f935f8,0xb4f9b5f8,0xb60033c9,0x3600b3c9,0xb5dcb584,0x35dc3584,0xb5ac35be,0x35acb5be,
0x34f935f8,0xb4f9b5f8,0xb60033c9,0x3600b3c9,0xb5dcb584,0x35dc3584,0xb5ac35be,0x35acb5be,0x35f8b4f9,0xb5f834f9,0x33c93600,0xb3c9b600,0xb58435dc,0x3584b5dc,0x35be35ac,0xb5beb5ac,
0x3f80,0x3f6dbec4,0x3f80,0x3f6dbec4,0x3ef13f62,0x3f22bf46,0xbef1bf62,0xbf223f46,0x3f553f0e,0x3e48bf7b,0x3f553f0e,0x3e48bf7b,0x3f7f3dc9,0xbe95bf75,0xbf7fbdc9,0x3e953f75,
0x3f808000,0xbec4bf6d,0x3f808000,0xbec4bf6d,0x3f62bef1,0xbf46bf22,0xbf623ef1,0x3f463f22,0x3f0ebf55,0xbf7bbe48,0x3f0ebf55,0xbf7bbe48,0x3dc9bf7f,0xbf753e95,0xbdc93f7f,0x3f75be95,
0x3f80,0xbf6d3ec4,0x3f80,0xbf6d3ec4,0x3f753e95,0x3dc93f7f,0xbf75be95,0xbdc9bf7f,0x3f0ebf55,0x3f7b3e48,0x3f0ebf55,0x3f7b3e48,0xbf22bf46,0x3ef1bf62,0x3f223f46,0xbef13f62,
0x3f808000,0x3ec43f6d,0x3f808000,0x3ec43f6d,0x3e95bf75,0x3f7fbdc9,0xbe953f75,0xbf7f3dc9,0xbf55bf0e,0x3e48bf7b,0xbf55bf0e,0x3e48bf7b,0xbf463f22,0xbf62bef1,0x3f46bf22,0x3f623ef1,
0x3f80,0x3f6dbec4,0x3f80,0x3f6dbec4,0x3f62bef1,0xbf46bf22,0xbf623ef1,0x3f463f22,0xbf55bf0e,0xbe483f7b,0xbf55bf0e,0xbe483f7b,0xbdc93f7f,0x3f75be95,0x3dc9bf7f,0xbf753e95,
0x3f808000,0xbec4bf6d,0x3f808000,0xbec4bf6d,0xbef1bf62,0xbf223f46,0x3ef13f62,0x3f22bf46,0xbf0e3f55,0x3f7b3e48,0xbf0e3f55,0x3f7b3e48,0x3f7f3dc9,0xbe95bf75,0xbf7fbdc9,0x3e953f75,
0x3f80,0xbf6d3ec4,0x3f80,0xbf6d3ec4,0x3e95bf75,0x3f7fbdc9,0xbe953f75,0xbf7f3dc9,0xbf0e3f55,0xbf7bbe48,0xbf0e3f55,0xbf7bbe48,0x3f46bf22,0x3f623ef1,0xbf463f22,0xbf62bef1,
0x3f808000,0x3ec43f6d,0x3f808000,0x3ec43f6d,0xbf75be95,0xbdc9bf7f,0x3f753e95,0x3dc93f7f,0x3f553f0e,0xbe483f7b,0x3f553f0e,0xbe483f7b,0xbf22bf46,0x3ef1bf62,0x3f223f46,0xbef13f62,
0x80003600,0x80003600,0xb5edb544,0xb5edb544,0x80003600,0x80003600,0x35ed3544,0x35ed3544,0x80003600,0x80003600,0xb5edb544,0xb5edb544,0x80003600,0x80003600,0x35ed3544,0x35ed3544,
0x36000000,0x36000000,0xb54435ed,0xb54435ed,0x36000000,0x36000000,0x3544b5ed,0x3544b5ed,0x36000000,0x36000000,0xb54435ed,0xb54435ed,0x36000000,0x36000000,0x3544b5ed,0x3544b5ed,
0xb57135e2,0x3571b5e2,0xb5a2b5c6,0x35a235c6,0xb5f53515,0x35f5b515,0xb44935ff,0x3449b5ff,0xb5e2b571,0x35e23571,0x35c6b5a2,0xb5c635a2,0xb515b5f5,0x351535f5,0xb5ffb449,0x35ff3449,
0x35e23571,0xb5e2b571,0xb5c635a2,0x35c6b5a2,0x351535f5,0xb515b5f5,0x35ff3449,0xb5ffb449,0xb57135e2,0x3571b5e2,0xb5a2b5c6,0x35a235c6,0xb5f53515,0x35f5b515,0xb44935ff,0x3449b5ff,
0xb5d5358e,0xb5d5358e,0xb4c8b5fb,0xb4c8b5fb,0xb58eb5d5,0xb58eb5d5,0xb5fb34c8,0xb5fb34c8,0x35d5b58e,0x35d5b58e,0x34c835fb,0x34c835fb,0x358e35d5,0x358e35d5,0x35fbb4c8,0x35fbb4c8,
0x358e35d5,0x358e35d5,0xb5fb34c8,0xb5fb34c8,0xb5d5358e,0xb5d5358e,0x34c835fb,0x34c835fb,0xb58eb5d5,0xb58eb5d5,0x35fbb4c8,0x35fbb4c8,0x35d5b58e,0x35d5b58e,0xb4c8b5fb,0xb4c8b5fb,
0xb5ff3449,0x35ffb449,0x3515b5f5,0xb51535f5,0x35a2b5c6,0xb5a235c6,0xb571b5e2,0x357135e2,0x344935ff,0xb449b5ff,0xb5f5b515,0x35f53515,0xb5c6b5a2,0x35c635a2,0xb5e23571,0x35e2b571,
0x344935ff,0xb449b5ff,0xb5f5b515,0x35f53515,0xb5c6b5a2,0x35c635a2,0xb5e23571,0x35e2b571,0x35ffb449,0xb5ff3449,0xb51535f5,0x3515b5f5,0xb5a235c6,0x35a2b5c6,0x357135e2,0xb571b5e2,
0x3f80,0x3f55bf0e,0x3f80,0x3f55bf0e,0x3f043f5c,0x3edbbf67,0xbf04bf5c,0xbedb3f67,0x3f623ef1,0xbdc9bf7f,0x3f623ef1,0xbdc9bf7f,0x3f80bd49,0xbf18bf4e,0xbf803d49,0x3f183f4e,
0x3f808000,0xbf0ebf55,0x3f808000,0xbf0ebf55,0x3f5cbf04,0xbf67bedb,0xbf5c3f04,0x3f673edb,0x3ef1bf62,0xbf7f3dc9,0x3ef1bf62,0xbf7f3dc9,0xbd49bf80,0xbf4e3f18,0x3d493f80,0x3f4ebf18,
0x3f80,0xbf553f0e,0x3f80,0xbf553f0e,0x3f783e79,0x3eac3f71,0xbf78be79,0xbeacbf71,0x3ef1bf62,0x3f7fbdc9,0x3ef1bf62,0x3f7fbdc9,0xbf3ebf2c,0x3e16bf7d,0x3f3e3f2c,0xbe163f7d,
0x3f808000,0x3f0e3f55,0x3f808000,0x3f0e3f55,0x3e79bf78,0x3f71beac,0xbe793f78,0xbf713eac,0xbf62bef1,0xbdc9bf7f,0xbf62bef1,0xbdc9bf7f,0xbf2c3f3e,0xbf7dbe16,0x3f2cbf3e,0x3f7d3e16,
0x3f80,0x3f55bf0e,0x3f80,0x3f55bf0e,0x3f5cbf04,0xbf67bedb,0xbf5c3f04,0x3f673edb,0xbf62bef1,0x3dc93f7f,0xbf62bef1,0x3dc93f7f,0x3d493f80,0x3f4ebf18,0xbd49bf80,0xbf4e3f18,
0x3f808000,0xbf0ebf55,0x3f808000,0xbf0ebf55,0xbf04bf5c,0xbedb3f67,0x3f043f5c,0x3edbbf67,0xbef13f62,0x3f7fbdc9,0xbef13f62,0x3f7fbdc9,0x3f80bd49,0xbf18bf4e,0xbf803d49,0x3f183f4e,
0x3f80,0xbf553f0e,0x3f80,0xbf553f0e,0x3e79bf78,0x3f71beac,0xbe793f78,0xbf713eac,0xbef13f62,0xbf7f3dc9,0xbef13f62,0xbf7f3dc9,0x3f2cbf3e,0x3f7d3e16,0xbf2c3f3e,0xbf7dbe16,
0x3f808000,0x3f0e3f55,0x3f808000,0x3f0e3f55,0xbf78be79,0xbeacbf71,0x3f783e79,0x3eac3f71,0x3f623ef1,0x3dc93f7f,0x3f623ef1,0x3dc93f7f,0xbf3ebf2c,0x3e16bf7d,0x3f3e3f2c,0xbe163f7d,
0x80003600,0x80003600,0xb5d5b58e,0xb5d5b58e,0x80003600,0x80003600,0x35d5358e,0x35d5358e,0x80003600,0x80003600,0xb5d5b58e,0xb5d5b58e,0x80003600,0x80003600,0x35d5358e,0x35d5358e,
0x36000000,0x36000000,0xb58e35d5,0xb58e35d5,0x36000000,0x36000000,0x358eb5d5,0x358eb5d5,0x36000000,0x36000000,0xb58e35d5,0xb58e35d5,0x36000000,0x36000000,0x358eb5d5,0x358eb5d5,
0xb58435dc,0x3584b5dc,0xb55bb5e7,0x355b35e7,0xb5f834f9,0x35f8b4f9,0xb52c35f1,0x352cb5f1,0xb5dcb584,0x35dc3584,0x35e7b55b,0xb5e7355b,0xb4f9b5f8,0x34f935f8,0xb5f1b52c,0x35f1352c,
0x35dc3584,0xb5dcb584,0xb5e7355b,0x35e7b55b,0x34f935f8,0xb4f9b5f8,0x35f1352c,0xb5f1b52c,0xb58435dc,0x3584b5dc,0xb55bb5e7,0x355b35e7,0xb5f834f9,0x35f8b4f9,0xb52c35f1,0x352cb5f1,
0xb5e23571,0xb5e23571,0x3449b5ff,0x3449b5ff,0xb571b5e2,0xb571b5e2,0xb5ffb449,0xb5ffb449,0x35e2b571,0x35e2b571,0xb44935ff,0xb44935ff,0x357135e2,0x357135e2,0x35ff3449,0x35ff3449,
0x357135e2,0x357135e2,0xb5ffb449,0xb5ffb449,0xb5e23571,0xb5e23571,0xb44935ff,0xb44935ff,0xb571b5e2,0xb571b5e2,0x35ff3449,0x35ff3449,0x35e2b571,0x35e2b571,0x3449b5ff,0x3449b5ff,
0xb600b3c9,0x360033c9,0x3598b5ce,0xb59835ce,0x35beb5ac,0xb5be35ac,0xb496b5fd,0x349635fd,0xb3c93600,0x33c9b600,0xb5ceb598,0x35ce3598,0xb5acb5be,0x35ac35be,0xb5fd3496,0x35fdb496,
0xb3c93600,0x33c9b600,0xb5ceb598,0x35ce3598,0xb5acb5be,0x35ac35be,0xb5fd3496,0x35fdb496,0x360033c9,0xb600b3c9,0xb59835ce,0x3598b5ce,0xb5be35ac,0x35beb5ac,0x349635fd,0xb496b5fd,
0x3f80,0x3f35bf35,0x3f80,0x3f35bf35,0x3f0e3f55,0x3e48bf7b,0xbf0ebf55,0xbe483f7b,0x3f6d3ec4,0xbec4bf6d,0x3f6d3ec4,0xbec4bf6d,0x3f7bbe48,0xbf55bf0e,0xbf7b3e48,0x3f553f0e,
0x3f808000,0xbf35bf35,0x3f808000,0xbf35bf35,0x3f55bf0e,0xbf7bbe48,0xbf553f0e,0x3f7b3e48,0x3ec4bf6d,0xbf6d3ec4,0x3ec4bf6d,0xbf6d3ec4,0xbe48bf7b,0xbf0e3f55,0x3e483f7b,0x3f0ebf55,
0x3f80,0xbf353f35,0x3f80,0xbf353f35,0x3f7b3e48,0x3f0e3f55,0xbf7bbe48,0xbf0ebf55,0x3ec4bf6d,0x3f6dbec4,0x3ec4bf6d,0x3f6dbec4,0xbf55bf0e,0xbe48bf7b,0x3f553f0e,0x3e483f7b,
0x3f808000,0x3f353f35,0x3f808000,0x3f353f35,0x3e48bf7b,0x3f55bf0e,0xbe483f7b,0xbf553f0e,0xbf6dbec4,0xbec4bf6d,0xbf6dbec4,0xbec4bf6d,0xbf0e3f55,0xbf7b3e48,0x3f0ebf55,0x3f7bbe48,
0x3f80,0x3f35bf35,0x3f80,0x3f35bf35,0x3f55bf0e,0xbf7bbe48,0xbf553f0e,0x3f7b3e48,0xbf6dbec4,0x3ec43f6d,0xbf6dbec4,0x3ec43f6d,0x3e483f7b,0x3f0ebf55,0xbe48bf7b,0xbf0e3f55,
0x3f808000,0xbf35bf35,0x3f808000,0xbf35bf35,0xbf0ebf55,0xbe483f7b,0x3f0e3f55,0x3e48bf7b,0xbec43f6d,0x3f6dbec4,0xbec43f6d,0x3f6dbec4,0x3f7bbe48,0xbf55bf0e,0xbf7b3e48,0x3f553f0e,
0x3f80,0xbf353f35,0x3f80,0xbf353f35,0x3e48bf7b,0x3f55bf0e,0xbe483f7b,0xbf553f0e,0xbec43f6d,0xbf6d3ec4,0xbec43f6d,0xbf6d3ec4,0x3f0ebf55,0x3f7bbe48,0xbf0e3f55,0xbf7b3e48,
0x3f808000,0x3f353f35,0x3f808000,0x3f353f35,0xbf7bbe48,0xbf0ebf55,0x3f7b3e48,0x3f0e3f55,0x3f6d3ec4,0x3ec43f6d,0x3f6d3ec4,0x3ec43f6d,0xbf55bf0e,0xbe48bf7b,0x3f553f0e,0x3e483f7b,
0x80003600,0x80003600,0xb5b5b5b5,0xb5b5b5b5,0x80003600,0x80003600,0x35b535b5,0x35b535b5,0x80003600,0x80003600,0xb5b5b5b5,0xb5b5b5b5,0x80003600,0x80003600,0x35b535b5,0x35b535b5,
0x36000000,0x36000000,0xb5b535b5,0xb5b535b5,0x36000000,0x36000000,0x35b5b5b5,0x35b5b5b5,0x36000000,0x36000000,0xb5b535b5,0xb5b535b5,0x36000000,0x36000000,0x35b5b5b5,0x35b5b5b5,
0xb58e35d5,0x358eb5d5,0xb4c8b5fb,0x34c835fb,0xb5fb34c8,0x35fbb4c8,0xb58e35d5,0x358eb5d5,0xb5d5b58e,0x35d5358e,0x35fbb4c8,0xb5fb34c8,0xb4c8b5fb,0x34c835fb,0xb5d5b58e,0x35d5358e,
0x35d5358e,0xb5d5b58e,0xb5fb34c8,0x35fbb4c8,0x34c835fb,0xb4c8b5fb,0x35d5358e,0xb5d5b58e,0xb58e35d5,0x358eb5d5,0xb4c8b5fb,0x34c835fb,0xb5fb34c8,0x35fbb4c8,0xb58e35d5,0x358eb5d5,
0xb5ed3544,0xb5ed3544,0x3544b5ed,0x3544b5ed,0xb544b5ed,0xb544b5ed,0xb5edb544,0xb5edb544,0x35edb544,0x35edb544,0xb54435ed,0xb54435ed,0x354435ed,0x354435ed,0x35ed3544,0x35ed3544,
0x354435ed,0x354435ed,0xb5edb544,0xb5edb544,0xb5ed3544,0xb5ed3544,0xb54435ed,0xb54435ed,0xb544b5ed,0xb544b5ed,0x35ed3544,0x35ed3544,0x35edb544,0x35edb544,0x3544b5ed,0x3544b5ed,
0xb5fbb4c8,0x35fb34c8,0x35d5b58e,0xb5d5358e,0x35d5b58e,0xb5d5358e,0x34c8b5fb,0xb4c835fb,0xb4c835fb,0x34c8b5fb,0xb58eb5d5,0x358e35d5,0xb58eb5d5,0x358e35d5,0xb5fbb4c8,0x35fb34c8,
0xb4c835fb,0x34c8b5fb,0xb58eb5d5,0x358e35d5,0xb58eb5d5,0x358e35d5,0xb5fbb4c8,0x35fb34c8,0x35fb34c8,0xb5fbb4c8,0xb5d5358e,0x35d5b58e,0xb5d5358e,0x35d5b58e,0xb4c835fb,0x34c8b5fb,
0x3f80,0x3f0ebf55,0x3f80,0x3f0ebf55,0x3f183f4e,0xbd49bf80,0xbf18bf4e,0x3d493f80,0x3f753e95,0xbf22bf46,0x3f753e95,0xbf22bf46,0x3f71beac,0xbf78be79,0xbf713eac,0x3f783e79,
0x3f808000,0xbf55bf0e,0x3f808000,0xbf55bf0e,0x3f4ebf18,0xbf803d49,0xbf4e3f18,0x3f80bd49,0x3e95bf75,0xbf463f22,0x3e95bf75,0xbf463f22,0xbeacbf71,0xbe793f78,0x3eac3f71,0x3e79bf78,
0x3f80,0xbf0e3f55,0x3f80,0xbf0e3f55,0x3f7d3e16,0x3f3e3f2c,0xbf7dbe16,0xbf3ebf2c,0x3e95bf75,0x3f46bf22,0x3e95bf75,0x3f46bf22,0xbf67bedb,0xbf04bf5c,0x3f673edb,0x3f043f5c,
0x3f808000,0x3f553f0e,0x3f808000,0x3f553f0e,0x3e16bf7d,0x3f2cbf3e,0xbe163f7d,0xbf2c3f3e,0xbf75be95,0xbf22bf46,0xbf75be95,0xbf22bf46,0xbedb3f67,0xbf5c3f04,0x3edbbf67,0x3f5cbf04,
0x3f80,0x3f0ebf55,0x3f80,0x3f0ebf55,0x3f4ebf18,0xbf803d49,0xbf4e3f18,0x3f80bd49,0xbf75be95,0x3f223f46,0xbf75be95,0x3f223f46,0x3eac3f71,0x3e79bf78,0xbeacbf71,0xbe793f78,
0x3f808000,0xbf55bf0e,0x3f808000,0xbf55bf0e,0xbf18bf4e,0x3d493f80,0x3f183f4e,0xbd49bf80,0xbe953f75,0x3f46bf22,0xbe953f75,0x3f46bf22,0x3f71beac,0xbf78be79,0xbf713eac,0x3f783e79,
0x3f80,0xbf0e3f55,0x3f80,0xbf0e3f55,0x3e16bf7d,0x3f2cbf3e,0xbe163f7d,0xbf2c3f3e,0xbe953f75,0xbf463f22,0xbe953f75,0xbf463f22,0x3edbbf67,0x3f5cbf04,0xbedb3f67,0xbf5c3f04,
0x3f808000,0x3f553f0e,0x3f808000,0x3f553f0e,0xbf7dbe16,0xbf3ebf2c,0x3f7d3e16,0x3f3e3f2c,0x3f753e95,0x3f223f46,0x3f753e95,0x3f223f46,0xbf67bedb,0xbf04bf5c,0x3f673edb,0x3f043f5c,
0x80003600,0x80003600,0xb58eb5d5,0xb58eb5d5,0x80003600,0x80003600,0x358e35d5,0x358e35d5,0x80003600,0x80003600,0xb58eb5d5,0xb58eb5d5,0x80003600,0x80003600,0x358e35d5,0x358e35d5,
0x36000000,0x36000000,0xb5d5358e,0xb5d5358e,0x36000000,0x36000000,0x35d5b58e,0x35d5b58e,0x36000000,0x36000000,0xb5d5358e,0xb5d5358e,0x36000000,0x36000000,0x35d5b58e,0x35d5b58e,
0xb59835ce,0x3598b5ce,0x33c9b600,0xb3c93600,0xb5fd3496,0x35fdb496,0xb5be35ac,0x35beb5ac,0xb5ceb598,0x35ce3598,0x360033c9,0xb600b3c9,0xb496b5fd,0x349635fd,0xb5acb5be,0x35ac35be,
0x35ce3598,0xb5ceb598,0xb600b3c9,0x360033c9,0x349635fd,0xb496b5fd,0x35ac35be,0xb5acb5be,0xb59835ce,0x3598b5ce,0x33c9b600,0xb3c93600,0xb5fd3496,0x35fdb496,0xb5be35ac,0x35beb5ac,
0xb5f53515,0xb5f53515,0x35a2b5c6,0x35a2b5c6,0xb515b5f5,0xb515b5f5,0xb5c6b5a2,0xb5c6b5a2,0x35f5b515,0x35f5b515,0xb5a235c6,0xb5a235c6,0x351535f5,0x351535f5,0x35c635a2,0x35c635a2,
0x351535f5,0x351535f5,0xb5c6b5a2,0xb5c6b5a2,0xb5f53515,0xb5f53515,0xb5a235c6,0xb5a235c6,0xb515b5f5,0xb515b5f5,0x35c635a2,0x35c635a2,0x35f5b515,0x35f5b515,0x35a2b5c6,0x35a2b5c6,
0xb5f1b52c,0x35f1352c,0x35f8b4f9,0xb5f834f9,0x35e7b55b,0xb5e7355b,0x3584b5dc,0xb58435dc,0xb52c35f1,0x352cb5f1,0xb4f9b5f8,0x34f935f8,0xb55bb5e7,0x355b35e7,0xb5dcb584,0x35dc3584,
0xb52c35f1,0x352cb5f1,0xb4f9b5f8,0x34f935f8,0xb55bb5e7,0x355b35e7,0xb5dcb584,0x35dc3584,0x35f1352c,0xb5f1b52c,0xb5f834f9,0x35f8b4f9,0xb5e7355b,0x35e7b55b,0xb58435dc,0x3584b5dc,
0x3f80,0x3ec4bf6d,0x3f80,0x3ec4bf6d,0x3f223f46,0xbe95bf75,0xbf22bf46,0x3e953f75,0x3f7b3e48,0xbf55bf0e,0x3f7b3e48,0xbf55bf0e,0x3f62bef1,0xbf7f3dc9,0xbf623ef1,0x3f7fbdc9,
0x3f808000,0xbf6dbec4,0x3f808000,0xbf6dbec4,0x3f46bf22,0xbf753e95,0xbf463f22,0x3f75be95,0x3e48bf7b,0xbf0e3f55,0x3e48bf7b,0xbf0e3f55,0xbef1bf62,0x3dc93f7f,0x3ef13f62,0xbdc9bf7f,
0x3f80,0xbec43f6d,0x3f80,0xbec43f6d,0x3f7f3dc9,0x3f623ef1,0xbf7fbdc9,0xbf62bef1,0x3e48bf7b,0x3f0ebf55,0x3e48bf7b,0x3f0ebf55,0xbf75be95,0xbf46bf22,0x3f753e95,0x3f463f22,
0x3f808000,0x3f6d3ec4,0x3f808000,0x3f6d3ec4,0x3dc9bf7f,0x3ef1bf62,0xbdc93f7f,0xbef13f62,0xbf7bbe48,0xbf55bf0e,0xbf7bbe48,0xbf55bf0e,0xbe953f75,0xbf223f46,0x3e95bf75,0x3f22bf46,
0x3f80,0x3ec4bf6d,0x3f80,0x3ec4bf6d,0x3f46bf22,0xbf753e95,0xbf463f22,0x3f75be95,0xbf7bbe48,0x3f553f0e,0xbf7bbe48,0x3f553f0e,0x3ef13f62,0xbdc9bf7f,0xbef1bf62,0x3dc93f7f,
0x3f808000,0xbf6dbec4,0x3f808000,0xbf6dbec4,0xbf22bf46,0x3e953f75,0x3f223f46,0xbe95bf75,0xbe483f7b,0x3f0ebf55,0xbe483f7b,0x3f0ebf55,0x3f62bef1,0xbf7f3dc9,0xbf623ef1,0x3f7fbdc9,
0x3f80,0xbec43f6d,0x3f80,0xbec43f6d,0x3dc9bf7f,0x3ef1bf62,0xbdc93f7f,0xbef13f62,0xbe483f7b,0xbf0e3f55,0xbe483f7b,0xbf0e3f55,0x3e95bf75,0x3f22bf46,0xbe953f75,0xbf223f46,
0x3f808000,0x3f6d3ec4,0x3f808000,0x3f6d3ec4,0xbf7fbdc9,0xbf62bef1,0x3f7f3dc9,0x3f623ef1,0x3f7b3e48,0x3f553f0e,0x3f7b3e48,0x3f553f0e,0xbf75be95,0xbf46bf22,0x3f753e95,0x3f463f22,
0x80003600,0x80003600,0xb544b5ed,0xb544b5ed,0x80003600,0x80003600,0x354435ed,0x354435ed,0x80003600,0x80003600,0xb544b5ed,0xb544b5ed,0x80003600,0x80003600,0x354435ed,0x354435ed,
0x36000000,0x36000000,0xb5ed3544,0xb5ed3544,0x36000000,0x36000000,0x35edb544,0x35edb544,0x36000000,0x36000000,0xb5ed3544,0xb5ed3544,0x36000000,0x36000000,0x35edb544,0x35edb544,
0xb5a235c6,0x35a2b5c6,0x3515b5f5,0xb51535f5,0xb5ff3449,0x35ffb449,0xb5e23571,0x35e2b571,0xb5c6b5a2,0x35c635a2,0x35f53515,0xb5f5b515,0xb449b5ff,0x344935ff,0xb571b5e2,0x357135e2,
0x35c635a2,0xb5c6b5a2,0xb5f5b515,0x35f53515,0x344935ff,0xb449b5ff,0x357135e2,0xb571b5e2,0xb5a235c6,0x35a2b5c6,0x3515b5f5,0xb51535f5,0xb5ff3449,0x35ffb449,0xb5e23571,0x35e2b571,
0xb5fb34c8,0xb5fb34c8,0x35d5b58e,0x35d5b58e,0xb4c8b5fb,0xb4c8b5fb,0xb58eb5d5,0xb58eb5d5,0x35fbb4c8,0x35fbb4c8,0xb5d5358e,0xb5d5358e,0x34c835fb,0x34c835fb,0x358e35d5,0x358e35d5,
0x34c835fb,0x34c835fb,0xb58eb5d5,0xb58eb5d5,0xb5fb34c8,0xb5fb34c8,0xb5d5358e,0xb5d5358e,0xb4c8b5fb,0xb4c8b5fb,0x358e35d5,0x358e35d5,0x35fbb4c8,0x35fbb4c8,0x35d5b58e,0x35d5b58e,
0xb5e2b571,0x35e23571,0x35ff3449,0xb5ffb449,0x35f5b515,0xb5f53515,0x35c6b5a2,0xb5c635a2,0xb57135e2,0x3571b5e2,0x3449b5ff,0xb44935ff,0xb515b5f5,0x351535f5,0xb5a2b5c6,0x35a235c6,
0xb57135e2,0x3571b5e2,0x3449b5ff,0xb44935ff,0xb515b5f5,0x351535f5,0xb5a2b5c6,0x35a235c6,0x35e23571,0xb5e2b571,0xb5ffb449,0x35ff3449,0xb5f53515,0x35f5b515,0xb5c635a2,0x35c6b5a2,
0x3f80,0x3e48bf7b,0x3f80,0x3e48bf7b,0x3f2c3f3e,0xbf04bf5c,0xbf2cbf3e,0x3f043f5c,0x3f7f3dc9,0xbf75be95,0x3f7f3dc9,0xbf75be95,0x3f4ebf18,0xbf673edb,0xbf4e3f18,0x3f67bedb,
0x3f808000,0xbf7bbe48,0x3f808000,0xbf7bbe48,0x3f3ebf2c,0xbf5c3f04,0xbf3e3f2c,0x3f5cbf04,0x3dc9bf7f,0xbe953f75,0x3dc9bf7f,0xbe953f75,0xbf18bf4e,0x3edb3f67,0x3f183f4e,0xbedbbf67,
0x3f80,0xbe483f7b,0x3f80,0xbe483f7b,0x3f803d49,0x3f783e79,0xbf80bd49,0xbf78be79,0x3dc9bf7f,0x3e95bf75,0x3dc9bf7f,0x3e95bf75,0xbf7dbe16,0xbf71beac,0x3f7d3e16,0x3f713eac,
0x3f808000,0x3f7b3e48,0x3f808000,0x3f7b3e48,0x3d49bf80,0x3e79bf78,0xbd493f80,0xbe793f78,0xbf7fbdc9,0xbf75be95,0xbf7fbdc9,0xbf75be95,0xbe163f7d,0xbeac3f71,0x3e16bf7d,0x3eacbf71,
0x3f80,0x3e48bf7b,0x3f80,0x3e48bf7b,0x3f3ebf2c,0xbf5c3f04,0xbf3e3f2c,0x3f5cbf04,0xbf7fbdc9,0x3f753e95,0xbf7fbdc9,0x3f753e95,0x3f183f4e,0xbedbbf67,0xbf18bf4e,0x3edb3f67,
0x3f808000,0xbf7bbe48,0x3f808000,0xbf7bbe48,0xbf2cbf3e,0x3f043f5c,0x3f2c3f3e,0xbf04bf5c,0xbdc93f7f,0x3e95bf75,0xbdc93f7f,0x3e95bf75,0x3f4ebf18,0xbf673edb,0xbf4e3f18,0x3f67bedb,
0x3f80,0xbe483f7b,0x3f80,0xbe483f7b,0x3d49bf80,0x3e79bf78,0xbd493f80,0xbe793f78,0xbdc93f7f,0xbe953f75,0xbdc93f7f,0xbe953f75,0x3e16bf7d,0x3eacbf71,0xbe163f7d,0xbeac3f71,
0x3f808000,0x3f7b3e48,0x3f808000,0x3f7b3e48,0xbf80bd49,0xbf78be79,0x3f803d49,0x3f783e79,0x3f7f3dc9,0x3f753e95,0x3f7f3dc9,0x3f753e95,0xbf7dbe16,0xbf71beac,0x3f7d3e16,0x3f713eac,
0x80003600,0x80003600,0xb4c8b5fb,0xb4c8b5fb,0x80003600,0x80003600,0x34c835fb,0x34c835fb,0x80003600,0x80003600,0xb4c8b5fb,0xb4c8b5fb,0x80003600,0x80003600,0x34c835fb,0x34c835fb,
0x36000000,0x36000000,0xb5fb34c8,0xb5fb34c8,0x36000000,0x36000000,0x35fbb4c8,0x35fbb4c8,0x36000000,0x36000000,0xb5fb34c8,0xb5fb34c8,0x36000000,0x36000000,0x35fbb4c8,0x35fbb4c8,
0xb5ac35be,0x35acb5be,0x3584b5dc,0xb58435dc,0xb60033c9,0x3600b3c9,0xb5f834f9,0x35f8b4f9,0xb5beb5ac,0x35be35ac,0x35dc3584,0xb5dcb584,0xb3c9b600,0x33c93600,0xb4f9b5f8,0x34f935f8,
0x35be35ac,0xb5beb5ac,0xb5dcb584,0x35dc3584,0x33c93600,0xb3c9b600,0x34f935f8,0xb4f9b5f8,0xb5ac35be,0x35acb5be,0x3584b5dc,0xb58435dc,0xb60033c9,0x3600b3c9,0xb5f834f9,0x35f8b4f9,
0xb5ff3449,0xb5ff3449,0x35f5b515,0x35f5b515,0xb449b5ff,0xb449b5ff,0xb515b5f5,0xb515b5f5,0x35ffb449,0x35ffb449,0xb5f53515,0xb5f53515,0x344935ff,0x344935ff,0x351535f5,0x351535f5,
0x344935ff,0x344935ff,0xb515b5f5,0xb515b5f5,0xb5ff3449,0xb5ff3449,0xb5f53515,0xb5f53515,0xb449b5ff,0xb449b5ff,0x351535f5,0x351535f5,0x35ffb449,0x35ffb449,0x35f5b515,0x35f5b515,
0xb5ceb598,0x35ce3598,0x35e7355b,0xb5e7b55b,0x35fdb496,0xb5fd3496,0x35f1b52c,0xb5f1352c,0xb59835ce,0x3598b5ce,0x355bb5e7,0xb55b35e7,0xb496b5fd,0x349635fd,0xb52cb5f1,0x352c35f1,
0xb59835ce,0x3598b5ce,0x355bb5e7,0xb55b35e7,0xb496b5fd,0x349635fd,0xb52cb5f1,0x352c35f1,0x35ce3598,0xb5ceb598,0xb5e7b55b,0x35e7355b,0xb5fd3496,0x35fdb496,0xb5f1352c,0x35f1b52c,
};

constexpr int TB_RF = 0, TB_RI = 14, TB_C8 = 26, TB_CB = 34, TB_END = 66;

__device__ __align__(1024) uint4 g_X[128 * 128 * 8];
__device__ __align__(1024) uint4 g_P[128 * 4 * 1024];
constexpr uint32_t T_W = 1000, T_PF = 1500;
constexpr uint32_t T_HALF = 250;
constexpr uint32_t T_Z0 = 1200, T_ZA = 950, T_ZB = 800;
constexpr uint32_t T_YA = 1200, T_YB = 1000;
constexpr uint32_t T_A0 = 550, T_A0B = 200, T_A1 = 500, T_A2 = 1700, T_A4 = 2900, T_RING = 900;
constexpr uint32_t T_PRE = 1000, T_LAST = 550;
constexpr uint32_t TM = 0x10001, TAG_Z = 1, TAG_Y = 0x10000, TAG_A = 0x10001, TAG_P = 0;
constexpr uint32_t POLLS = 200000;

__device__ __forceinline__ void wgmma_ss_n224(float (&d)[112], uint64_t da, uint64_t db, int sd) {
  asm volatile("{\n.reg .pred p;\nsetp.ne.b32 p, %114, 0;\n"
    "wgmma.mma_async.sync.aligned.m64n224k16.f32.bf16.bf16 {%0, %1, %2, %3, %4, %5, %6, %7, %8, %9, %10, %11, %12, %13, %14, %15, %16, %17, %18, %19, %20, %21, %22, %23, %24, %25, %26, %27, %28, %29, %30, %31, %32, %33, %34, %35, %36, %37, %38, %39, %40, %41, %42, %43, %44, %45, %46, %47, %48, %49, %50, %51, %52, %53, %54, %55, %56, %57, %58, %59, %60, %61, %62, %63, %64, %65, %66, %67, %68, %69, %70, %71, %72, %73, %74, %75, %76, %77, %78, %79, %80, %81, %82, %83, %84, %85, %86, %87, %88, %89, %90, %91, %92, %93, %94, %95, %96, %97, %98, %99, %100, %101, %102, %103, %104, %105, %106, %107, %108, %109, %110, %111}, %112, %113, p, 1, 1, 0, 1;\n}\n"
    : "+f"(d[0]), "+f"(d[1]), "+f"(d[2]), "+f"(d[3]), "+f"(d[4]), "+f"(d[5]), "+f"(d[6]), "+f"(d[7]), "+f"(d[8]), "+f"(d[9]), "+f"(d[10]), "+f"(d[11]), "+f"(d[12]), "+f"(d[13]), "+f"(d[14]), "+f"(d[15]), "+f"(d[16]), "+f"(d[17]), "+f"(d[18]), "+f"(d[19]), "+f"(d[20]), "+f"(d[21]), "+f"(d[22]), "+f"(d[23]), "+f"(d[24]), "+f"(d[25]), "+f"(d[26]), "+f"(d[27]), "+f"(d[28]), "+f"(d[29]), "+f"(d[30]), "+f"(d[31]), "+f"(d[32]), "+f"(d[33]), "+f"(d[34]), "+f"(d[35]), "+f"(d[36]), "+f"(d[37]), "+f"(d[38]), "+f"(d[39]), "+f"(d[40]), "+f"(d[41]), "+f"(d[42]), "+f"(d[43]), "+f"(d[44]), "+f"(d[45]), "+f"(d[46]), "+f"(d[47]), "+f"(d[48]), "+f"(d[49]), "+f"(d[50]), "+f"(d[51]), "+f"(d[52]), "+f"(d[53]), "+f"(d[54]), "+f"(d[55]), "+f"(d[56]), "+f"(d[57]), "+f"(d[58]), "+f"(d[59]), "+f"(d[60]), "+f"(d[61]), "+f"(d[62]), "+f"(d[63]), "+f"(d[64]), "+f"(d[65]), "+f"(d[66]), "+f"(d[67]), "+f"(d[68]), "+f"(d[69]), "+f"(d[70]), "+f"(d[71]), "+f"(d[72]), "+f"(d[73]), "+f"(d[74]), "+f"(d[75]), "+f"(d[76]), "+f"(d[77]), "+f"(d[78]), "+f"(d[79]), "+f"(d[80]), "+f"(d[81]), "+f"(d[82]), "+f"(d[83]), "+f"(d[84]), "+f"(d[85]), "+f"(d[86]), "+f"(d[87]), "+f"(d[88]), "+f"(d[89]), "+f"(d[90]), "+f"(d[91]), "+f"(d[92]), "+f"(d[93]), "+f"(d[94]), "+f"(d[95]), "+f"(d[96]), "+f"(d[97]), "+f"(d[98]), "+f"(d[99]), "+f"(d[100]), "+f"(d[101]), "+f"(d[102]), "+f"(d[103]), "+f"(d[104]), "+f"(d[105]), "+f"(d[106]), "+f"(d[107]), "+f"(d[108]), "+f"(d[109]), "+f"(d[110]), "+f"(d[111])
    : "l"(da), "l"(db), "r"(sd));
}

__device__ __forceinline__ void wgmma_rs_n128(float (&d)[64], uint32_t a0, uint32_t a1, uint32_t a2, uint32_t a3, uint64_t db, int sd) {
  asm volatile("{\n.reg .pred p;\nsetp.ne.b32 p, %69, 0;\n"
    "wgmma.mma_async.sync.aligned.m64n128k16.f32.bf16.bf16 {%0, %1, %2, %3, %4, %5, %6, %7, %8, %9, %10, %11, %12, %13, %14, %15, %16, %17, %18, %19, %20, %21, %22, %23, %24, %25, %26, %27, %28, %29, %30, %31, %32, %33, %34, %35, %36, %37, %38, %39, %40, %41, %42, %43, %44, %45, %46, %47, %48, %49, %50, %51, %52, %53, %54, %55, %56, %57, %58, %59, %60, %61, %62, %63}, {%64, %65, %66, %67}, %68, p, 1, 1, 1;\n}\n"
    : "+f"(d[0]), "+f"(d[1]), "+f"(d[2]), "+f"(d[3]), "+f"(d[4]), "+f"(d[5]), "+f"(d[6]), "+f"(d[7]), "+f"(d[8]), "+f"(d[9]), "+f"(d[10]), "+f"(d[11]), "+f"(d[12]), "+f"(d[13]), "+f"(d[14]), "+f"(d[15]), "+f"(d[16]), "+f"(d[17]), "+f"(d[18]), "+f"(d[19]), "+f"(d[20]), "+f"(d[21]), "+f"(d[22]), "+f"(d[23]), "+f"(d[24]), "+f"(d[25]), "+f"(d[26]), "+f"(d[27]), "+f"(d[28]), "+f"(d[29]), "+f"(d[30]), "+f"(d[31]), "+f"(d[32]), "+f"(d[33]), "+f"(d[34]), "+f"(d[35]), "+f"(d[36]), "+f"(d[37]), "+f"(d[38]), "+f"(d[39]), "+f"(d[40]), "+f"(d[41]), "+f"(d[42]), "+f"(d[43]), "+f"(d[44]), "+f"(d[45]), "+f"(d[46]), "+f"(d[47]), "+f"(d[48]), "+f"(d[49]), "+f"(d[50]), "+f"(d[51]), "+f"(d[52]), "+f"(d[53]), "+f"(d[54]), "+f"(d[55]), "+f"(d[56]), "+f"(d[57]), "+f"(d[58]), "+f"(d[59]), "+f"(d[60]), "+f"(d[61]), "+f"(d[62]), "+f"(d[63])
    : "r"(a0), "r"(a1), "r"(a2), "r"(a3), "l"(db), "r"(sd));
}


__device__ __forceinline__ void mbar_init(uint32_t bar, uint32_t cnt) { asm volatile("mbarrier.init.shared::cta.b64 [%0], %1;" :: "r"(bar), "r"(cnt)); }
__device__ __forceinline__ void mbar_expect(uint32_t bar, uint32_t bytes) { asm volatile("mbarrier.arrive.expect_tx.shared::cta.b64 _, [%0], %1;" :: "r"(bar), "r"(bytes) : "memory"); }
__device__ __forceinline__ void mbar_arrive(uint32_t bar) { asm volatile("mbarrier.arrive.shared::cta.b64 _, [%0];" :: "r"(bar) : "memory"); }
__device__ __forceinline__ void mbar_arrive_remote(uint32_t bar) { asm volatile("mbarrier.arrive.relaxed.cluster.shared::cluster.b64 _, [%0];" :: "r"(bar) : "memory"); }
__device__ __forceinline__ void mbar_wait(uint32_t bar, uint32_t ph) {
  asm volatile("{\n.reg .pred p,q;\n.reg .u32 n;\nmov.u32 n, 0;\nLW%=:\nmbarrier.try_wait.parity.shared::cta.b64 p, [%0], %1;\n"
               "add.u32 n, n, 1;\nsetp.lt.and.u32 q, n, 200000, !p;\n@q bra LW%=;\n}\n" :: "r"(bar), "r"(ph) : "memory");
}
__device__ __forceinline__ void mbar_wait2(uint32_t bar, uint32_t ph, uint32_t bar2, uint32_t ph2) {
  asm volatile("{\n.reg .pred p,q,r;\n.reg .u32 n;\nmov.u32 n, 0;\nLW%=:\nmbarrier.try_wait.parity.shared::cta.b64 p, [%0], %1;\n"
               "mbarrier.try_wait.parity.shared::cta.b64 r, [%2], %3;\nand.pred p,p,r;\nadd.u32 n, n, 1;\n"
               "setp.lt.and.u32 q, n, 200000, !p;\n@q bra LW%=;\n}\n" :: "r"(bar), "r"(ph), "r"(bar2), "r"(ph2) : "memory");
}
__device__ __forceinline__ void wg_fence() { asm volatile("wgmma.fence.sync.aligned;" ::: "memory"); }
__device__ __forceinline__ void wg_commit() { asm volatile("wgmma.commit_group.sync.aligned;" ::: "memory"); }
__device__ __forceinline__ void wg_wait0() { asm volatile("wgmma.wait_group.sync.aligned 0;" ::: "memory"); }
__device__ __forceinline__ void tma2d(uint32_t dst, const CUtensorMap* tm, uint32_t bar, int c0, int c1) {
  asm volatile("cp.async.bulk.tensor.2d.shared::cluster.global.mbarrier::complete_tx::bytes [%0], [%1, {%3,%4}], [%2];"
               :: "r"(dst), "l"(tm), "r"(bar), "r"(c0), "r"(c1) : "memory");
}
__device__ __forceinline__ void tma3d(uint32_t dst, const CUtensorMap* tm, uint32_t bar, int c0) {
  asm volatile("cp.async.bulk.tensor.3d.shared::cluster.global.mbarrier::complete_tx::bytes [%0], [%1, {%3,%4,%4}], [%2];"
               :: "r"(dst), "l"(tm), "r"(bar), "r"(c0), "r"(0) : "memory");
}
__device__ __forceinline__ void tma4a(uint32_t dst, const CUtensorMap* tm, uint32_t bar, int c2, int c3) {
  asm volatile("cp.async.bulk.tensor.4d.shared::cluster.global.mbarrier::complete_tx::bytes [%0], [%1, {%5,%5,%3,%4}], [%2];"
               :: "r"(dst), "l"(tm), "r"(bar), "r"(c2), "r"(c3), "r"(0) : "memory");
}
__device__ __forceinline__ uint32_t clk() { uint32_t t; asm volatile("mov.u32 %0, %%clock;" : "=r"(t) :: "memory"); return t; }
__device__ __forceinline__ void tma4d(uint32_t dst, const CUtensorMap* tm, uint32_t bar, int c0, int c2) {
  asm volatile("cp.async.bulk.tensor.4d.shared::cluster.global.mbarrier::complete_tx::bytes [%0], [%1, {%3,%5,%4,%5}], [%2];"
               :: "r"(dst), "l"(tm), "r"(bar), "r"(c0), "r"(c2), "r"(0) : "memory");
}
__device__ __forceinline__ void tma5d(uint32_t dst, const CUtensorMap* tm, uint32_t bar, int c2, int c4) {
  asm volatile("cp.async.bulk.tensor.5d.shared::cluster.global.mbarrier::complete_tx::bytes [%0], [%1, {%5,%5,%3,%5,%4}], [%2];"
               :: "r"(dst), "l"(tm), "r"(bar), "r"(c2), "r"(c4), "r"(0) : "memory");
}
__device__ __forceinline__ uint64_t mkdesc(uint32_t addr, uint32_t lbo, uint32_t sbo) {
  return (uint64_t)((addr & 0x3FFFF) >> 4) | ((uint64_t)(lbo >> 4) << 16) | ((uint64_t)(sbo >> 4) << 32) | (1ull << 62);
}
__device__ __forceinline__ uint32_t pack(float lo, float hi) { uint32_t r; asm("cvt.rn.bf16x2.f32 %0, %1, %2;" : "=r"(r) : "f"(hi), "f"(lo)); return r; }
template <uint32_t TAG> __device__ __forceinline__ uint32_t pack_tag(float lo, float hi) {
  uint32_t r; asm("cvt.rz.bf16x2.f32 %0, %1, %2;" : "=r"(r) : "f"(hi), "f"(lo));
  return ((r + (~TAG & TM)) & ~TM) | TAG;
}
__device__ __forceinline__ uint32_t pack_relu(float lo, float hi) { uint32_t r; asm("cvt.rn.relu.bf16x2.f32 %0, %1, %2;" : "=r"(r) : "f"(hi), "f"(lo)); return r; }
__device__ __forceinline__ uint32_t mul2(uint32_t a, uint32_t b) { uint32_t r; asm("mul.rn.bf16x2 %0, %1, %2;" : "=r"(r) : "r"(a), "r"(b)); return r; }
__device__ __forceinline__ uint32_t add2(uint32_t a, uint32_t b) { uint32_t r; asm("add.rn.bf16x2 %0, %1, %2;" : "=r"(r) : "r"(a), "r"(b)); return r; }
__device__ __forceinline__ uint4 add2v(uint4 a, uint4 b) { return make_uint4(add2(a.x, b.x), add2(a.y, b.y), add2(a.z, b.z), add2(a.w, b.w)); }
__device__ __forceinline__ float blo(uint32_t w) { return __uint_as_float(w << 16); }
__device__ __forceinline__ float bhi(uint32_t w) { return __uint_as_float(w & 0xffff0000u); }
__device__ __forceinline__ float uf(uint32_t w) { return __uint_as_float(w); }
template <int N> __device__ __forceinline__ void fence_regs(float (&d)[N]) {
#pragma unroll
  for (int i = 0; i < N; i++) asm volatile("" : "+f"(d[i]) :: "memory");
}
template <int N> __device__ __forceinline__ void def_regs(uint32_t (&d)[N]) {
#pragma unroll
  for (int i = 0; i < N; i++) asm volatile("mov.b32 %0, 0;" : "=r"(d[i]));
}
#define PHASE_IDS int lane = lane_; asm volatile("" : "+r"(lane)); const int g = lane >> 2, q = lane & 3; (void)q; (void)g;
__device__ __forceinline__ uint4 ld_relaxed(const uint4* p) { uint4 v; asm volatile("ld.relaxed.gpu.global.v4.u32 {%0,%1,%2,%3}, [%4];" : "=r"(v.x), "=r"(v.y), "=r"(v.z), "=r"(v.w) : "l"(p) : "memory"); return v; }
__device__ __forceinline__ void st_relaxed(uint4* p, uint32_t x, uint32_t y, uint32_t z, uint32_t w) { asm volatile("st.relaxed.gpu.global.v4.u32 [%0], {%1,%2,%3,%4};" :: "l"(p), "r"(x), "r"(y), "r"(z), "r"(w) : "memory"); }
__device__ __forceinline__ uint32_t ld_w(const uint32_t* p) { uint32_t v; asm volatile("ld.global.L2::128B.u32 %0, [%1];" : "=r"(v) : "l"(p) : "memory"); return v; }
__device__ __forceinline__ uint4 ld_g(const uint4* p) { uint4 v; asm volatile("ld.global.v4.u32 {%0,%1,%2,%3}, [%4];" : "=r"(v.x), "=r"(v.y), "=r"(v.z), "=r"(v.w) : "l"(p) : "memory"); return v; }
__device__ __forceinline__ uint4 lds(uint32_t a) { uint4 v; asm volatile("ld.shared.v4.u32 {%0,%1,%2,%3}, [%4];" : "=r"(v.x), "=r"(v.y), "=r"(v.z), "=r"(v.w) : "r"(a) : "memory"); return v; }
__device__ __forceinline__ void sts(uint32_t a, uint32_t x, uint32_t y, uint32_t z, uint32_t w) { asm volatile("st.shared.v4.u32 [%0], {%1,%2,%3,%4};" :: "r"(a), "r"(x), "r"(y), "r"(z), "r"(w) : "memory"); }
__device__ __forceinline__ uint2 lds64(uint32_t a) { uint2 v; asm volatile("ld.shared.v2.u32 {%0,%1}, [%2];" : "=r"(v.x), "=r"(v.y) : "r"(a) : "memory"); return v; }
__device__ __forceinline__ void wbar(int wg) { asm volatile("bar.sync %0, 128;" :: "r"(4 + wg) : "memory"); }
__device__ __forceinline__ void cbar() { asm volatile("bar.sync 1, 256;" ::: "memory"); }
__device__ __forceinline__ void mma0(float (&d)[4], uint32_t a0, uint32_t a1, uint32_t a2, uint32_t a3, uint32_t b0, uint32_t b1) {
  asm("mma.sync.aligned.m16n8k16.row.col.f32.bf16.bf16.f32 {%0,%1,%2,%3}, {%4,%5,%6,%7}, {%8,%9}, {%10,%10,%10,%10};"
      : "=f"(d[0]), "=f"(d[1]), "=f"(d[2]), "=f"(d[3]) : "r"(a0), "r"(a1), "r"(a2), "r"(a3), "r"(b0), "r"(b1), "f"(0.f));
}
__device__ __forceinline__ void mma1(float (&d)[4], uint32_t a0, uint32_t a1, uint32_t a2, uint32_t a3, uint32_t b0, uint32_t b1) {
  asm("mma.sync.aligned.m16n8k16.row.col.f32.bf16.bf16.f32 {%0,%1,%2,%3}, {%4,%5,%6,%7}, {%8,%9}, {%0,%1,%2,%3};"
      : "+f"(d[0]), "+f"(d[1]), "+f"(d[2]), "+f"(d[3]) : "r"(a0), "r"(a1), "r"(a2), "r"(a3), "r"(b0), "r"(b1));
}
__device__ __forceinline__ uint32_t wd(const uint4& v, int i) { return i == 0 ? v.x : i == 1 ? v.y : i == 2 ? v.z : v.w; }
template <uint32_t TAG> __device__ __forceinline__ void cdft16(const uint4 (&m)[4], const uint4 (&a)[4], uint4 (&o)[4]) {
#pragma unroll
  for (int nt = 0; nt < 4; nt++) {
    float c[2][4];
#pragma unroll
    for (int mu = 0; mu < 2; mu++) {
      mma0(c[mu], a[mu].x, a[mu].y, a[mu].z, a[mu].w, wd(m[nt >> 1], 2 * (nt & 1)), wd(m[nt >> 1], 2 * (nt & 1) + 1));
      mma1(c[mu], a[2 + mu].x, a[2 + mu].y, a[2 + mu].z, a[2 + mu].w, wd(m[2 + (nt >> 1)], 2 * (nt & 1)), wd(m[2 + (nt >> 1)], 2 * (nt & 1) + 1));
    }
    o[nt] = make_uint4(pack_tag<TAG>(c[0][0], c[0][1]), pack(c[0][2], c[0][3]), pack(c[1][0], c[1][1]), pack(c[1][2], c[1][3]));
  }
}
__device__ __forceinline__ void mma8(float (&d)[4], uint32_t a0, uint32_t a1, uint32_t b0, bool first) {
  if (first) asm("mma.sync.aligned.m16n8k8.row.col.f32.bf16.bf16.f32 {%0,%1,%2,%3}, {%4,%5}, {%6}, {%7,%7,%7,%7};"
                 : "=f"(d[0]), "=f"(d[1]), "=f"(d[2]), "=f"(d[3]) : "r"(a0), "r"(a1), "r"(b0), "f"(0.f));
  else asm("mma.sync.aligned.m16n8k8.row.col.f32.bf16.bf16.f32 {%0,%1,%2,%3}, {%4,%5}, {%6}, {%0,%1,%2,%3};"
           : "+f"(d[0]), "+f"(d[1]), "+f"(d[2]), "+f"(d[3]) : "r"(a0), "r"(a1), "r"(b0));
}
__device__ __forceinline__ void cdft16v(const uint4 (&m)[4], const uint4 (&v)[4], uint4 (&o)[4]) {
#pragma unroll
  for (int nt = 0; nt < 4; nt++) {
    float c[2][4];
#pragma unroll
    for (int i = 0; i < 4; i++) {
      const uint32_t b = wd(m[(i >> 1) * 2 + (nt >> 1)], 2 * (nt & 1) + (i & 1));
      mma8(c[0], v[i].x, v[i].y, b, i == 0);
      mma8(c[1], v[i].z, v[i].w, b, i == 0);
    }
    o[nt] = make_uint4(pack(c[0][0], c[0][1]), pack(c[0][2], c[0][3]), pack(c[1][0], c[1][1]), pack(c[1][2], c[1][3]));
  }
}
__device__ __forceinline__ void ld_pred(uint4& v, const uint4* p, uint32_t c) {
  asm volatile("{.reg .pred p; setp.ne.u32 p, %5, 0;\n@p ld.relaxed.gpu.global.v4.u32 {%0,%1,%2,%3}, [%4];}"
               : "+r"(v.x), "+r"(v.y), "+r"(v.z), "+r"(v.w) : "l"(p), "r"(c) : "memory");
}
__device__ __forceinline__ void lds_pred(uint4& v, uint32_t a, uint32_t c) {
  asm volatile("{.reg .pred p; setp.ne.u32 p, %5, 0;\n@p ld.shared.v4.u32 {%0,%1,%2,%3}, [%4];}"
               : "+r"(v.x), "+r"(v.y), "+r"(v.z), "+r"(v.w) : "r"(a), "r"(c) : "memory");
}
__device__ __forceinline__ void st_pred(uint4* p, const uint4& v, uint32_t c) {
  asm volatile("{.reg .pred p; setp.ne.u32 p, %5, 0;\n@p st.relaxed.gpu.global.v4.u32 [%4], {%0,%1,%2,%3};}"
               :: "r"(v.x), "r"(v.y), "r"(v.z), "r"(v.w), "l"(p), "r"(c) : "memory");
}
__device__ __forceinline__ uint32_t warm_tick() {
  uint32_t r;
  asm volatile("{\n.reg .b32 z;\n.reg .f32 d0,d1,d2,d3,e;\nmov.b32 z, 0;\nmov.f32 e, 0f00000000;\n"
               "mma.sync.aligned.m16n8k8.row.col.f32.bf16.bf16.f32 {d0,d1,d2,d3}, {z,z}, {z}, {e,e,e,e};\nmov.b32 %0, d0;\n}\n" : "=r"(r) :: "memory");
  return r;
}
__device__ __forceinline__ void mbar_wait_warm(uint32_t bar, uint32_t ph) {
#pragma unroll 1
  for (uint32_t n = 0; n < 2000000; n++) {
    uint32_t ok;
    n += warm_tick();
    asm volatile("{.reg .pred p; mbarrier.test_wait.parity.shared::cta.b64 p, [%1], %2; selp.u32 %0, 1, 0, p;}" : "=r"(ok) : "r"(bar), "r"(ph) : "memory");
    if (__all_sync(0xffffffffu, ok)) break;
    __nanosleep(150);
  }
}
__device__ __forceinline__ void wait_until(uint32_t t0, uint32_t delay) { while (clk() - t0 < delay) {} }
template <int ID, int N, class F> __device__ __forceinline__ void repoll(uint4 (&v)[N], uint32_t tag, uint32_t tm, F addr) {
  for (uint32_t n = 0; n < POLLS; n++) {
    uint32_t bad = 0;
#pragma unroll
    for (int i = 0; i < N; i++) bad |= v[i].x ^ tag;
    if (!__any_sync(0xffffffffu, bad & tm)) break;
#pragma unroll
    for (int i = 0; i < N; i++) ld_pred(v[i], addr(i), (v[i].x ^ tag) & tm);
  }
}
__device__ __forceinline__ void acc_stats(const uint4& x, float& s, float& ss) {
#pragma unroll
  for (int k = 0; k < 4; k++) {
    const float lo = blo(wd(x, k)), hi = bhi(wd(x, k));
    s += lo + hi; ss = fmaf(lo, lo, fmaf(hi, hi, ss));
  }
}
__device__ __forceinline__ uint32_t fma2(uint32_t a, uint32_t b, uint32_t c) { uint32_t r; asm("fma.rn.bf16x2 %0, %1, %2, %3;" : "=r"(r) : "r"(a), "r"(b), "r"(c)); return r; }

constexpr int STAGE = 32768;
constexpr int SM_ST = 131072, SM_BAR = SM_ST + 3 * STAGE, SM_TOTAL = SM_BAR + 3072;
constexpr int SM_W = 0, SM_X = 32768, SM_M = 49152, SM_IN = 65536, SM_E = 65536, SM_P0 = SM_ST + 2 * STAGE,
              SM_T = 81920 - TB_RI * 512, SM_X2 = 114688, SM_RF = SM_P0 + 16384;
struct Params {
  const uint32_t* x; const uint4* tab; uint4* X; uint4* Pp; uint32_t* out;
  const char *wg, *wu, *wdn;
  CUtensorMap a, g2, g1, gh, u2, u1, uh, w192, w32, wr, wi;
};

__global__ void __cluster_dims__(2, 1, 1) __launch_bounds__(384, 1) fused_kernel(const __grid_constant__ Params P) {
  extern __shared__ __align__(1024) char sm[];
  if (threadIdx.x < 128) asm volatile("prefetch.global.L2 [%0];" :: "l"(P.x + (size_t)(blockIdx.x + 128 * (threadIdx.x >> 3)) * 256 + (threadIdx.x & 7) * 32) : "memory");
  uint32_t s0;
  asm volatile("{.reg .u64 t; cvta.to.shared.u64 t, %1; cvt.u32.u64 %0, t;}" : "=r"(s0) : "l"(sm));
  const uint32_t barA = s0 + SM_BAR,
      barF = barA + 64, barE = barF + 32,
      barW = barE + 32, barX = barW + 32,
      barR = barX + 32,
      barD = barR + 8,
      barO = barD + 8,
      barV = barO + 8, barM = barV + 8,
      barG = barM + 8, barS = barG + 8,
      barN = barS + 16, barC = barN + 16,
      barQ = barC + 8, barP = barQ + 8,
      barU = barP + 16,
      barT = barU + 16, barI = barT + 64,
      barZ = barT;
  const int cta = blockIdx.x, rb = cta >> 3, jf = cta & 7;
  const int warp = __shfl_sync(0xffffffffu, threadIdx.x >> 5, 0), lane = threadIdx.x & 31;
  const uint32_t tstart = clk();
  const int pr = jf >> 1, odd = jf & 1;
  const int atom0 = 7 * pr + (odd ? 4 : 0);
  const int halfcol = (7 * pr + 3) * 64 + odd * 32;
  const uint32_t ring = s0 + SM_ST;
  if (warp >= 8) {
    asm volatile("setmaxnreg.dec.sync.aligned.u32 104;");
    if (threadIdx.x == 256) {
      for (int i = 0; i < 8; i++) { mbar_init(barA + 8 * i, 1); mbar_init(barT + 8 * i, 1); }
      for (int i = 0; i < 32; i++) mbar_init(barI + 8 * i, 1);
      for (int i = 0; i < 3; i++) { mbar_init(barF + 8 * i, 1); mbar_init(barE + 8 * i, 2); }
      for (int i = 0; i < 4; i++) { mbar_init(barW + 8 * i, 2); mbar_init(barX + 8 * i, 2); }
      for (int i = 0; i < 2; i++) { mbar_init(barS + 8 * i, 8); mbar_init(barN + 8 * i, 1); mbar_init(barP + 8 * i, 1); mbar_init(barU + 8 * i, 2 - i); }
      mbar_init(barR, 2); mbar_init(barD, 8); mbar_init(barO, 1); mbar_init(barV, 1); mbar_init(barM, 4); mbar_init(barG, 8); mbar_init(barQ, 8);
      asm volatile("fence.mbarrier_init.release.cluster;" ::: "memory");
    }
    __syncwarp();
    asm volatile("barrier.cluster.arrive.relaxed.aligned;" ::: "memory");
    if (warp == 11 && lane < 11) asm volatile("prefetch.tensormap [%0];" :: "l"(&P.a + lane) : "memory");
    uint32_t mw[8];
    {
      const int g = lane >> 2, q = lane & 3, inv = (warp >> 1) & 1, kt = warp & 1;
#pragma unroll
      for (int k = 0; k < 8; k++) {
        const int oi = (g >> 1) + 4 * (k >> 1);
        int n = (inv ? (cta + 128 * oi) * (4 * (2 * kt + (k & 1)) + q) : oi * (cta + 128 * (2 * (q + 4 * kt) + (k & 1)))) & 2047;
        n = n > 1024 ? n - 2048 : n;
        float sn, cs;
        __sincosf((float)n * (6.283185307179586f / 2048.f), &sn, &cs);
        if (!inv) sn = -sn;
        mw[k] = (g & 1) ? pack(sn, cs) : pack(cs, -sn);
      }
    }
    const uint32_t mad = s0 + SM_M + (warp - 8) * 1024 + lane * 16;
    sts(mad, mw[0], mw[1], mw[2], mw[3]); sts(mad + 512, mw[4], mw[5], mw[6], mw[7]);
    asm volatile("barrier.cluster.wait.acquire.aligned;" ::: "memory");
    if (lane == 0) mbar_arrive(barM);
    if (warp != 8) {
      if (threadIdx.x == 320) {
        wait_until(tstart, T_PF);
        asm volatile("cp.async.bulk.prefetch.L2.global [%0], 14336;" :: "l"(P.wg + cta * 14336) : "memory");
        mbar_wait(barS + 8, 0);
        asm volatile("cp.async.bulk.prefetch.L2.global [%0], 14336;" :: "l"(P.wu + cta * 14336) : "memory");
      }
      __syncwarp();
      uint32_t tph = 0;
#pragma unroll 1
      for (int layer = 0; layer < 2; layer++) {
        if (layer) {
          if (warp == 11) mbar_wait_warm(barD, 0); else mbar_wait(barD, 0);
          sts(mad, mw[0], mw[1], mw[2], mw[3]); sts(mad + 512, mw[4], mw[5], mw[6], mw[7]);
          __syncwarp();
          if (lane == 0) mbar_arrive(barM);
        }
        if (warp == 11) mbar_wait_warm(barG, layer); else mbar_wait(barG, layer);
        const uint32_t t0 = clk(), tag = layer ^ 1;
        if (warp == 11) { while (__any_sync(0xffffffffu, clk() - t0 + warm_tick() < 1200)) __nanosleep(50); }
        asm volatile("fence.proxy.async.shared::cta;" ::: "memory");
#pragma unroll 1
        for (int k = warp - 8; k < 8; k += 3) {
          wait_until(t0, k == 1 ? T_A1 : k < 4 ? T_A2 : T_A4);
#pragma unroll 1
          for (uint32_t n = 0; n < POLLS; n++) {
            if (lane == 0) { mbar_expect(barT + 8 * k, 16384); tma4a(s0 + k * 16384, &P.a, barT + 8 * k, rb * 8, k); }
            mbar_wait(barT + 8 * k, (tph >> k) & 1);
            tph ^= 1u << k;
            uint32_t all1 = TM;
#pragma unroll
            for (int i = 0; i < 32; i++) {
              uint32_t w;
              asm volatile("ld.shared.u32 %0, [%1];" : "=r"(w) : "r"(s0 + k * 16384 + i * 512 + lane * 16) : "memory");
              all1 &= w;
            }
            const bool bad = __any_sync(0xffffffffu, all1 != TAG_A);
            if (!bad) break;
          }
          if (lane == 0) mbar_arrive(barA + 8 * k);
        }
        if (layer == 0 && threadIdx.x == 320) asm volatile("cp.async.bulk.prefetch.L2.global [%0], 14336;" :: "l"(P.wdn + cta * 14336) : "memory");
        __syncwarp();
        if (warp < 11) {
          const int c = warp - 9;
          const uint32_t bp = barP + c * 8, pb = s0 + (c ^ 1) * SM_P0 + lane * 16;
          mbar_wait(barX + 8 + 8 * c, layer);
          wait_until(clk(), T_PRE);
          bool seen = false;
#pragma unroll 1
          for (uint32_t n = 0; n < POLLS; n++) {
            if (lane == 0) {
              mbar_expect(bp, 16384);
              asm volatile("cp.async.bulk.shared::cluster.global.mbarrier::complete_tx::bytes [%0], [%1], 16384, [%2];"
                           :: "r"(pb), "l"(P.Pp + cta * 4096 + c * 1024), "r"(bp) : "memory");
            }
            mbar_wait2(barN + 8 * c, layer, bp, (tph >> 8) & 1);
            tph ^= 256;
            if (c == 0 && !seen) {
              uint32_t w;
              asm volatile("ld.shared.u32 %0, [%1];" : "=r"(w) : "r"(s0 + SM_P0 + (lane & 7) * 2048) : "memory");
              seen = !__any_sync(0xffffffffu, ((w ^ tag) & 1) && (lane & 7) != jf);
              if (seen && lane == 0) mbar_arrive(barZ);
            }
            mbar_wait(barX + 24, layer);
            uint32_t bad = 0;
#pragma unroll 2
            for (int k = 0; k < 4; k++) {
              uint4 rw[8];
#pragma unroll
              for (int i = 0; i < 8; i++) {
                rw[i] = lds((i == 0 ? s0 + SM_IN + jf * 8192 + c * 2048 + lane * 16 : pb + ((pr ^ i) & 3) * 4096 + ((odd ^ (i >> 2)) << 11)) + k * 512);
                bad |= rw[i].x ^ tag;
              }
#pragma unroll
              for (int r = 0; r < 2; r++) {
                const uint4 u = add2v(add2v(rw[4 * r], rw[4 * r + 1]), add2v(rw[4 * r + 2], rw[4 * r + 3]));
                sts(pb + (pr ^ 1) * 4096 + ((odd ^ r) << 11) + k * 512, u.x, u.y, u.z, u.w);
              }
            }
            if (!__any_sync(0xffffffffu, bad & 1)) break;
            asm volatile("fence.proxy.async.shared::cta;" ::: "memory");
            __syncwarp();
          }
          __syncwarp();
          if (lane == 0) mbar_arrive(barU);
        } else if (lane == 0) {
          mbar_wait(barX + 8, layer);
          mbar_expect(barU + 8, TB_RI * 512);
          asm volatile("cp.async.bulk.shared::cluster.global.mbarrier::complete_tx::bytes [%0], [%1], %3, [%2];" :: "r"(s0 + SM_RF), "l"(P.tab), "r"(barU + 8), "n"(TB_RI * 512) : "memory");
        }
        __syncwarp();
      }
    } else {
      uint32_t eph = 0;
      auto ldw = [&](uint32_t dst, int c, int snd) {
        const int col = (2 * c + (odd ^ snd)) * 64;
        mbar_expect(barW + 8 * c, 28672);
        tma2d(dst, &P.w192, barW + 8 * c, col, atom0 * 64); tma2d(dst + 24576, &P.w32, barW + 8 * c, col, halfcol);
      };
#pragma unroll 1
      for (int layer = 0; layer < 2; layer++) {
        if (layer) {
          __syncwarp();
          mbar_wait(barD, 0);
          sts(mad, mw[0], mw[1], mw[2], mw[3]); sts(mad + 512, mw[4], mw[5], mw[6], mw[7]);
          __syncwarp();
        }
        if (lane != 0) continue;
        if (layer) { mbar_arrive(barM); mbar_wait(barQ, 0); } else wait_until(tstart, T_W);
        mbar_expect(barV, 20480 + (TB_END - TB_RI) * 512);
        asm volatile("cp.async.bulk.shared::cluster.global.mbarrier::complete_tx::bytes [%0], [%1], %3, [%2];" :: "r"(s0 + SM_T + TB_RI * 512), "l"(P.tab + TB_RI * 32), "r"(barV), "n"((TB_END - TB_RI) * 512) : "memory");
        tma3d(s0 + SM_W, &P.wr, barV, (rb * 257 + 32 * jf + 1) & ~7);
        tma3d(s0 + SM_W + 10240, &P.wi, barV, (rb * 257 + 32 * jf + 1) & ~7);
        int s = 0;
#pragma unroll 1
        for (int it = 0; it < 19; it++) {
          const uint32_t dst = ring + s * STAGE, bf = barF + 8 * s;
          if (it >= 3) { mbar_wait(barE + 8 * s, (eph >> s) & 1); eph ^= 1u << s; }
          else {
            mbar_wait(it == 2 ? barG : barS + 8 * it, layer);
            if (it == 2) wait_until(clk(), T_RING);
          }
          if (it < 8) {
            mbar_expect(bf, 28672);
            tma5d(dst, &P.g2, bf, it * 4, atom0);
            tma5d(dst + 16384, &P.u1, bf, it * 4, atom0);
            tma4d(dst + 24576, &P.gh, bf, halfcol, it * 4);
          } else if (it < 16) {
            mbar_expect(bf, 28672);
            tma5d(dst, &P.u2, bf, (it - 8) * 4, atom0 + 1);
            tma5d(dst + 16384, &P.g1, bf, (it - 8) * 4, atom0 + 2);
            tma4d(dst + 24576, &P.uh, bf, halfcol, (it - 8) * 4);
            if (it == 12 || it == 14) ldw(s0 + (it - 12) * 16384, 0, it == 14);
          } else {
            ldw(dst, it == 18 ? 2 : 1, it > 16);
          }
          if (++s == 3) s = 0;
        }
        mbar_wait(barX, layer);
        ldw(s0, 2, 0); ldw(s0 + 32768, 3, 0);
        mbar_wait(barX + 8, layer);
        ldw(ring + STAGE, 3, 1);
      }
    }
  } else {
    const int wg = warp >> 2, lane_ = lane;
    uint32_t peer;
    asm("mapa.shared::cluster.u32 %0, %1, %2;" : "=r"(peer) : "r"(s0), "r"(odd ^ 1));
    uint4 xr[2][2];
    {
      const uint32_t* xp = P.x + (size_t)(cta + 256 * warp) * 256 + (lane & 3) * 32 + (lane >> 2);
#pragma unroll
      for (int k = 0; k < 4; k++) xr[k & 1][k >> 1].x = ld_w(xp + (k & 1) * (128 * 256) + (k >> 1) * 128);
#pragma unroll
      for (int k = 0; k < 4; k++) {
        const uint32_t* p = xp + (k & 1) * (128 * 256) + (k >> 1) * 128;
        xr[k & 1][k >> 1].y = ld_w(p + 8); xr[k & 1][k >> 1].z = ld_w(p + 16); xr[k & 1][k >> 1].w = ld_w(p + 24);
      }
    }
    uint4 f1[4], twa[4], twb[2], f2[4];
    auto load_rf = [&](const uint4* tab) {
#pragma unroll
      for (int k = 0; k < 4; k++) { f1[k] = ld_g(tab + (TB_RF + k) * 32); twa[k] = ld_g(tab + (TB_RF + 4 + k) * 32); }
      twb[0] = ld_g(tab + (TB_RF + 8) * 32); twb[1] = ld_g(tab + (TB_RF + 9) * 32);
#pragma unroll
      for (int k = 0; k < 4; k++) f2[k] = ld_g(tab + (TB_RF + 10 + k) * 32);
    };
    load_rf(P.tab + lane);
    asm volatile("barrier.cluster.arrive.relaxed.aligned;" ::: "memory");
    asm volatile("setmaxnreg.inc.sync.aligned.u32 200;");
    uint32_t fph = 0;
    float sx[2] = {0.f, 0.f}, sq[2] = {0.f, 0.f};
    acc_stats(xr[0][0], sx[0], sq[0]); acc_stats(xr[1][0], sx[1], sq[1]);
    if (wg == 1) asm volatile("bar.arrive 2, 256;" ::: "memory");
    asm volatile("barrier.cluster.wait.acquire.aligned;" ::: "memory");
#pragma unroll 1
    for (int layer = 0; layer < 2; layer++) {
      const uint32_t tag = layer ^ 1;
      uint32_t t0;
      float mean[2];
      uint4 *pR, *pC;
      {
        PHASE_IDS
        float rstd[2];
        acc_stats(xr[0][1], sx[0], sq[0]); acc_stats(xr[1][1], sx[1], sq[1]);
        {
          const bool h1 = lane & 16, h2 = lane & 8;
          float p = (h1 ? sq[0] : sx[0]) + __shfl_xor_sync(0xffffffffu, h1 ? sx[0] : sq[0], 16);
          float r_ = (h1 ? sq[1] : sx[1]) + __shfl_xor_sync(0xffffffffu, h1 ? sx[1] : sq[1], 16);
          float v = (h2 ? r_ : p) + __shfl_xor_sync(0xffffffffu, h2 ? p : r_, 8);
          v += __shfl_xor_sync(0xffffffffu, v, 4); v += __shfl_xor_sync(0xffffffffu, v, 2); v += __shfl_xor_sync(0xffffffffu, v, 1);
          sx[0] = __shfl_sync(0xffffffffu, v, 0); sx[1] = __shfl_sync(0xffffffffu, v, 8);
          sq[0] = __shfl_sync(0xffffffffu, v, 16); sq[1] = __shfl_sync(0xffffffffu, v, 24);
        }
#pragma unroll
        for (int r = 0; r < 2; r++) {
          mean[r] = sx[r] * (1.f / 512.f);
          rstd[r] = rsqrtf(fmaxf(fmaf(-mean[r], mean[r], sq[r] * (1.f / 512.f)), 0.f) + 1e-5f);
        }
        uint32_t xw[2][4][2];
#pragma unroll
        for (int r = 0; r < 2; r++) {
          float c[2][2][4];
#pragma unroll
          for (int e = 0; e < 2; e++) {
            const uint32_t sel = e ? 0x7632 : 0x5410;
            const uint32_t b00 = __byte_perm(xr[r][0].x, xr[r][0].y, sel), b01 = __byte_perm(xr[r][0].z, xr[r][0].w, sel);
            const uint32_t b10 = __byte_perm(xr[r][1].x, xr[r][1].y, sel), b11 = __byte_perm(xr[r][1].z, xr[r][1].w, sel);
#pragma unroll
            for (int mt = 0; mt < 2; mt++) {
              mma0(c[mt][e], f1[mt * 2].x, f1[mt * 2].y, f1[mt * 2].z, f1[mt * 2].w, b00, b01);
              mma1(c[mt][e], f1[mt * 2 + 1].x, f1[mt * 2 + 1].y, f1[mt * 2 + 1].z, f1[mt * 2 + 1].w, b10, b11);
            }
          }
          uint32_t tl[2][2], th[2][2], t1[2][2];
#pragma unroll
          for (int e = 0; e < 2; e++)
#pragma unroll
            for (int i = 0; i < 2; i++) {
              const uint4 k = twa[e * 2 + i];
              const float re = c[0][e][i], im = c[0][e][2 + i];
              tl[e][i] = pack(fmaf(uf(k.x), re, uf(k.y) * im), fmaf(uf(k.z), re, uf(k.w) * im));
              const uint32_t spc = pack(fmaf(mean[r], -32.f, re), 0.f);
              th[e][i] = g == 0 ? spc : tl[e][i];
              const float cc = uf(wd(twb[e], 2 * i)), sn = uf(wd(twb[e], 2 * i + 1));
              const float r1 = c[1][e][i], i1 = c[1][e][2 + i];
              t1[e][i] = pack(fmaf(cc, r1, sn * i1), fmaf(cc, i1, -sn * r1));
            }
          const float rs = rstd[r];
#pragma unroll
          for (int nt = 0; nt < 4; nt++) {
            float d[4];
            mma0(d, nt < 2 ? tl[0][0] : th[0][0], t1[0][0], nt < 2 ? tl[0][1] : th[0][1], t1[0][1], wd(f2[nt >> 1], 2 * (nt & 1)), wd(f2[nt >> 1], 2 * (nt & 1) + 1));
            mma1(d, nt < 2 ? tl[1][0] : th[1][0], t1[1][0], nt < 2 ? tl[1][1] : th[1][1], t1[1][1], wd(f2[2 + (nt >> 1)], 2 * (nt & 1)), wd(f2[2 + (nt >> 1)], 2 * (nt & 1) + 1));
            xw[r][nt][0] = pack(d[0] * rs, d[1] * rs); xw[r][nt][1] = pack(d[2] * rs, d[3] * rs);
          }
        }
        mbar_wait(barM, layer);
        const uint32_t sw = (g ^ (2 * ((q ^ warp) & 3))) << 4;
#pragma unroll
        for (int nt = 0; nt < 4; nt++)
          sts(s0 + SM_X + warp * 2048 + q * 256 + sw + (nt & 1) * 1024 + (nt >> 1) * 128, xw[0][nt][0], xw[0][nt][1], xw[1][nt][0], xw[1][nt][1]);
        uint4 mi[4];
#pragma unroll
        for (int k = 0; k < 4; k++) mi[k] = lds(s0 + SM_M + k * 512 + lane * 16);
        const int kb = (warp & 3) + (g & 4), vec = (warp & 4) + (g & 3);
        pR = P.X + ((q * 8 + kb) * 128 + cta) * 8 + vec;
        pC = P.X + (cta * 128 + q * 8 + kb) * 8 + vec;
        const uint32_t xa = s0 + SM_X + q * 2048 + kb * 256 + ((vec ^ (2 * ((q ^ kb) & 3))) << 4);
        cbar();
        if (wg == 1) wait_until(clk(), T_HALF);
        uint4 v[4], o[4];
#pragma unroll
        for (int k = 0; k < 4; k++) v[k] = lds(xa + (k >> 1) * 8192 + (k & 1) * 128);
        cdft16<TAG_Z>(mi, v, o);
#pragma unroll
        for (int k = 0; k < 4; k++) st_relaxed(pR + k * 32768, o[k].x, o[k].y, o[k].z, o[k].w);
        t0 = clk() - 80;
      }
      {
        PHASE_IDS
        const int kb = (warp & 3) + (g & 4);
        const uint32_t eb = s0 + SM_E + wg * 8192;
        uint32_t e1 = eb + kb * 1024 + (q >> 1) * 128 + ((((q & 1) * 4 + (g & 3)) ^ (2 * ((kb ^ (q >> 1)) & 3))) << 4);
        uint32_t e2 = eb + q * 1024 + (warp & 3) * 256 + (((g >> 1) ^ (2 * ((q ^ (2 * warp)) & 3))) << 4) + (g & 1) * 8;
        uint32_t e3 = eb + q * 1024 + (warp & 3) * 256 + ((((g & 1) * 4 + (g >> 1)) ^ q ^ (4 * (warp & 1))) << 4);
        uint32_t e4 = eb + kb * 1024 + q * 128 + (((g & 3) ^ (kb & 3) ^ (2 * q)) << 4);
        asm volatile("" : "+r"(e1), "+r"(e2), "+r"(e3), "+r"(e4));
        uint4 v[4], o[4], a[4];
        mbar_wait(barV, layer);
        uint4 mb[4], mbi[4], f8[4], f8i[4];
        const uint32_t tb = s0 + SM_T + lane * 16;
#pragma unroll
        for (int k = 0; k < 4; k++) {
          mb[k] = lds(tb + (TB_C8 + k) * 512); mbi[k] = lds(tb + (TB_C8 + 4 + k) * 512);
          f8[k] = lds(tb + (TB_CB + (warp & 3) * 8 + 2 * k) * 512); f8i[k] = lds(tb + (TB_CB + (warp & 3) * 8 + 2 * k + 1) * 512);
        }
        wait_until(t0, layer ? (wg ? T_ZB : T_ZA) : T_Z0);
#pragma unroll
        for (int k = 0; k < 4; k++) v[k] = ld_relaxed(pC + k * 256);
        float wf[32];
        {
          const int col = (warp & 4) + (g >> 1);
          const int k0 = (g & 1) ? 31 - col : (col == 0 ? 15 : col - 1), k1 = (g & 1) ? 23 - col : col + 7;
          const float hz = (jf == 7 && k0 == 31) ? 0.5f : 1.f;
          const uint32_t wa0 = s0 + SM_W + ((warp & 3) * 32 + q) * 80 + ((rb + 1) & 7) * 2;
          mbar_wait(barV, layer);
#pragma unroll
          for (int v = 0; v < 8; v++)
#pragma unroll
            for (int e = 0; e < 2; e++) {
              const uint32_t ad = wa0 + (e ? k1 : k0) * 2 + ((v >> 1) * 8 + 4 * (v & 1)) * 80;
              uint32_t wa, wb;
              asm volatile("ld.shared.u16 %0, [%1];" : "=r"(wa) : "r"(ad) : "memory");
              asm volatile("ld.shared.u16 %0, [%1+10240];" : "=r"(wb) : "r"(ad) : "memory");
              wf[v * 4 + 2 * e] = e == 0 ? blo(wa) * hz : blo(wa);
              wf[v * 4 + 2 * e + 1] = e == 0 ? blo(wb) * hz : blo(wb);
            }
        }
        repoll<0>(v, TAG_Z, TM, [&](int k) { return pC + k * 256; });
        if (lane == 0) mbar_arrive(barS);
        cdft16v(mb, v, o);
#pragma unroll
        for (int k = 0; k < 4; k++) sts((e1 ^ ((k & 1) << 6)) + k * 256, o[k].x, o[k].y, o[k].z, o[k].w);
        wbar(wg);
#pragma unroll
        for (int ap = 0; ap < 4; ap++) {
          const uint32_t ad = (e2 ^ ((ap & 1) << 6) ^ ((ap >> 1) << 5)) + (ap >> 1) * 128;
          const uint2 l0 = lds64(ad), l1 = lds64(ad + 4096);
          a[ap] = make_uint4(l0.x, l0.y, l1.x, l1.y);
        }
        uint32_t ow[4][2][2];
#pragma unroll
        for (int ap = 0; ap < 4; ap++) {
          uint32_t pw[2][2];
#pragma unroll
          for (int t = 0; t < 2; t++) {
            float c[4];
            mma0(c, a[ap].x, a[ap].y, a[ap].z, a[ap].w, wd(f8[ap], 2 * t), wd(f8[ap], 2 * t + 1));
#pragma unroll
            for (int e = 0; e < 2; e++) {
              const float wa = wf[(ap * 2 + t) * 4 + 2 * e], wb = wf[(ap * 2 + t) * 4 + 2 * e + 1], re = c[2 * e], im = c[2 * e + 1];
              pw[t][e] = pack(fmaf(re, wa, -im * wb), fmaf(re, wb, im * wa));
            }
          }
#pragma unroll
          for (int t = 0; t < 2; t++) {
            float c[4];
            mma0(c, pw[0][0], pw[0][1], pw[1][0], pw[1][1], wd(f8i[ap], 2 * t), wd(f8i[ap], 2 * t + 1));
            ow[ap][t][0] = pack(c[0], c[1]); ow[ap][t][1] = pack(c[2], c[3]);
          }
        }
#pragma unroll
        for (int k = 0; k < 4; k++) {
          const int pp = k >> 1, t = k & 1;
          sts((e3 ^ (pp << 5)) + pp * 128 + t * 4096, ow[2 * pp][t][0], ow[2 * pp][t][1], ow[2 * pp + 1][t][0], ow[2 * pp + 1][t][1]);
        }
        wbar(wg);
#pragma unroll
        for (int k = 0; k < 4; k++) a[k] = lds((e4 ^ ((k & 1) << 6)) + (k >> 1) * 512);
        cdft16<TAG_Y>(mbi, a, o);
#pragma unroll
        for (int k = 0; k < 4; k++) st_relaxed(pC + k * 256, o[k].x, o[k].y, o[k].z, o[k].w);
        t0 = clk() - 80;
      }
      float vs[2];
      {
        PHASE_IDS
        uint4 v[4], o[4], mii[4];
#pragma unroll
        for (int k = 0; k < 4; k++) mii[k] = lds(s0 + SM_M + 2048 + k * 512 + lane * 16);
        uint4 g2[4], twi[4], g1[4];
#pragma unroll
        for (int k = 0; k < 4; k++) {
          const uint32_t tb = s0 + SM_T + (TB_RI + k) * 512 + lane * 16;
          g2[k] = lds(tb); twi[k] = lds(tb + 2048); g1[k] = lds(tb + 4096);
        }
        float y[2][4][4];
#pragma unroll
        for (int r = 0; r < 2; r++)
#pragma unroll
          for (int k = 0; k < 8; k++) {
            const uint32_t w = wd(xr[r][k >> 2], k & 3);
            y[r][k >> 1][k & 1] = blo(w) - mean[r]; y[r][k >> 1][2 + (k & 1)] = bhi(w) - mean[r];
          }
        uint32_t x1 = s0 + SM_X2 + q * 1024 + ((warp & 3) + (g & 4)) * 128 + ((((warp & 4) + (g & 3)) ^ (2 * ((q ^ warp) & 3))) << 4);
        uint32_t x2 = s0 + SM_X2 + warp * 2048 + q * 128 + ((g ^ (2 * (((2 * warp) ^ q) & 3))) << 4);
        uint4* ap = P.X + ((warp * 16 + q) * 128 + cta) * 8 + g;
        const uint4* sp = P.X + ((lane >> 3) * 1024 + rb * 8 + warp) * 8 + (lane & 7);
        asm volatile("" : "+r"(x1), "+r"(x2), "+l"(ap), "+l"(sp));
#pragma unroll
        for (int i = 0; i < 8; i++) fence_regs(y[i >> 2][i & 3]);
        wait_until(t0, wg ? T_YB : T_YA);
#pragma unroll
        for (int k = 0; k < 4; k++) v[k] = ld_relaxed(pR + k * 32768);
        repoll<1>(v, TAG_Y, TM, [&](int k) { return pR + k * 32768; });
        if (lane == 0) mbar_arrive(barS + 8);
        cdft16v(mii, v, o);
#pragma unroll
        for (int k = 0; k < 4; k++) sts(x1 + k * 4096, o[k].x, o[k].y, o[k].z, o[k].w);
        cbar();
#pragma unroll
        for (int k = 0; k < 4; k++) v[k] = lds((x2 ^ ((k >> 1) << 5)) + (k >> 1) * 1024 + (k & 1) * 512);
        const float nsp = q == 0 ? 0.f : 1.f;
#pragma unroll
        for (int r = 0; r < 2; r++) {
          const uint4 v0 = v[2 * r], v1 = v[2 * r + 1];
          uint32_t T[2][2][2];
#pragma unroll
          for (int mt = 0; mt < 2; mt++) {
            float lo[4], hi[4], c1[4];
            mma0(lo, g2[mt * 2].x, g2[mt * 2].y, g2[mt * 2].z, g2[mt * 2].w, v0.x, v1.x);
            mma0(hi, g2[mt * 2 + 1].x, g2[mt * 2 + 1].y, g2[mt * 2 + 1].z, g2[mt * 2 + 1].w, v0.z, v1.z);
            mma0(c1, g2[mt * 2].x, g2[mt * 2].y, g2[mt * 2].z, g2[mt * 2].w, v0.y, v1.y);
            mma1(c1, g2[mt * 2 + 1].x, g2[mt * 2 + 1].y, g2[mt * 2 + 1].z, g2[mt * 2 + 1].w, v0.w, v1.w);
            {
              const uint4 k = twi[mt * 2];
              float re = fmaf(hi[0], nsp, lo[0]), im = fmaf(hi[2], nsp, lo[2]);
              float tr = fmaf(re, uf(k.x), -im * uf(k.y)), ti = fmaf(re, uf(k.y), im * uf(k.x));
              T[mt][0][0] = pack(q == 0 ? hi[0] : tr, q == 0 ? tr : ti);
              re = lo[1] + hi[1]; im = lo[3] + hi[3];
              T[mt][0][1] = pack(fmaf(re, uf(k.z), -im * uf(k.w)), fmaf(re, uf(k.w), im * uf(k.z)));
            }
            {
              const uint4 k = twi[mt * 2 + 1];
              T[mt][1][0] = pack(fmaf(c1[0], uf(k.x), -c1[2] * uf(k.y)), fmaf(c1[0], uf(k.y), c1[2] * uf(k.x)));
              T[mt][1][1] = pack(fmaf(c1[1], uf(k.z), -c1[3] * uf(k.w)), fmaf(c1[1], uf(k.w), c1[3] * uf(k.z)));
            }
          }
#pragma unroll
          for (int nt = 0; nt < 4; nt++) {
            mma1(y[r][nt], T[0][0][0], T[1][0][0], T[0][0][1], T[1][0][1], wd(g1[nt >> 1], 2 * (nt & 1)), wd(g1[nt >> 1], 2 * (nt & 1) + 1));
            mma1(y[r][nt], T[0][1][0], T[1][1][0], T[0][1][1], T[1][1][1], wd(g1[2 + (nt >> 1)], 2 * (nt & 1)), wd(g1[2 + (nt >> 1)], 2 * (nt & 1) + 1));
          }
        }
        uint4 aw[4];
#pragma unroll
        for (int k = 0; k < 4; k++) {
          const int r = k & 1, st = k >> 1;
          aw[k] = make_uint4(pack_tag<TAG_A>(y[r][2 * st][0], y[r][2 * st][2]), pack(y[r][2 * st][1], y[r][2 * st][3]),
                             pack(y[r][2 * st + 1][0], y[r][2 * st + 1][2]), pack(y[r][2 * st + 1][1], y[r][2 * st + 1][3]));
          if (st == 0) st_pred(ap + r * 8192, aw[k], q < 2);
        }
        t0 = clk() - 40;
        if (lane == 0) mbar_arrive(barG);
        if (lane < 4) mbar_expect(barI + warp * 32 + 8 * lane, 2048);
#pragma unroll
        for (int r = 0; r < 2; r++) {
          float c0 = 0.f, c1 = 0.f;
#pragma unroll
          for (int k = 0; k < 8; k++) { c0 = fmaf(y[r][k >> 1][k & 1], y[r][k >> 1][k & 1], c0); c1 = fmaf(y[r][k >> 1][2 + (k & 1)], y[r][k >> 1][2 + (k & 1)], c1); }
          vs[r] = c0 + c1;
#pragma unroll
          for (int st = 0; st < 2; st++)
            xr[r][st] = make_uint4(pack(y[r][2 * st][0] + mean[r], y[r][2 * st][2] + mean[r]), pack(y[r][2 * st][1] + mean[r], y[r][2 * st][3] + mean[r]),
                                   pack(y[r][2 * st + 1][0] + mean[r], y[r][2 * st + 1][2] + mean[r]), pack(y[r][2 * st + 1][1] + mean[r], y[r][2 * st + 1][3] + mean[r]));
        }
        uint4 av[4];
        uint32_t ad = s0 + (warp * 16 + (lane >> 3)) * 128 + (((lane & 7) ^ (lane >> 3)) << 4);
        asm volatile("" : "+r"(ad));
        wait_until(t0, T_A0 + wg * T_A0B);
#pragma unroll
        for (int i = 0; i < 4; i++) av[i] = ld_relaxed(sp + i * 32768);
#pragma unroll
        for (int k = 0; k < 2; k++) st_pred(ap + k * 8192, aw[k], q >= 2);
        repoll<2>(av, TAG_A, TM, [&](int i) { return sp + i * 32768; });
#pragma unroll
        for (int i = 0; i < 4; i++) sts((ad ^ ((i & 1) << 6)) + i * 512, av[i].x, av[i].y, av[i].z, av[i].w);
        asm volatile("fence.proxy.async.shared::cta;" ::: "memory");
#pragma unroll
        for (int k = 2; k < 4; k++) st_relaxed(ap + (k & 1) * 8192 + 4096, aw[k].x, aw[k].y, aw[k].z, aw[k].w);
      }
      uint32_t h[56];
      const bool el = (threadIdx.x & 127) == 0;
      const uint32_t myT = 2 + wg, otT = 3 - wg;
      PHASE_IDS
      const uint32_t inA0 = s0 + SM_IN + warp * 8192, inB0 = barI + warp * 32;
      const uint32_t outA = inA0 - s0 + peer, outB = inB0 - s0 + peer, peerR = barR - s0 + peer;
      uint32_t voff0 = (g * 8 + (q ^ ((g & 1) << 2) ^ (2 * odd))) * 16;
      char* gdst = (char*)(P.Pp + (rb * 8 + warp) * 4096 + pr * 256) + odd * 2048;
      asm volatile("" : "+r"(voff0));
      {
        const uint64_t dA0 = mkdesc(s0 + wg * 8192, 16, 1024);
        int s = 0;
        float acc[112];
        auto kstep = [&](int it, int first, uint32_t ba) {
          mbar_wait2(ba, layer, barF + 8 * s, (fph >> s) & 1);
          fph ^= 1u << s;
          const uint64_t dB = mkdesc(ring + s * STAGE, 8192, 1024), dA = dA0 + (uint64_t)(it * 1024);
          asm volatile("bar.sync %0, 256;" :: "r"(myT) : "memory");
          wg_fence();
#pragma unroll
          for (int k = 0; k < 4; k++) wgmma_ss_n224(acc, dA + 2 * k, dB + 128 * k, !(first && k == 0));
          wg_commit();
          asm volatile("bar.arrive %0, 256;" :: "r"(otT) : "memory");
          wg_wait0();
          if (el) mbar_arrive(barE + 8 * s);
          if (++s == 3) s = 0;
        };
        kstep(0, 1, barM);
#pragma unroll 1
        for (int it = 1; it < 8; it++) kstep(it, 0, barA + 8 * it);
        fence_regs(acc);
#pragma unroll
        for (int i = 0; i < 16; i++) {
          h[i] = mul2(pack_relu(acc[2 * i], acc[2 * i + 1]), pack(acc[64 + 2 * i], acc[64 + 2 * i + 1]));
          h[16 + i] = pack_relu(acc[32 + 2 * i], acc[32 + 2 * i + 1]);
        }
#pragma unroll
        for (int i = 0; i < 8; i++) h[48 + i] = pack_relu(acc[96 + 2 * i], acc[96 + 2 * i + 1]);
        kstep(0, 1, barG);
#pragma unroll 1
        for (int it = 1; it < 6; it++) kstep(it, 0, barG);
        {
          mbar_wait(barF + 16, (fph >> 2) & 1);
          const uint64_t dB = mkdesc(ring + s * STAGE, 8192, 1024), dC = dB - (2 * STAGE >> 4), dA = dA0 + (uint64_t)((s + 4) * 1024);
          asm volatile("bar.sync %0, 256;" :: "r"(myT) : "memory");
          wg_fence();
#pragma unroll
          for (int k = 0; k < 4; k++) wgmma_ss_n224(acc, dA + 2 * k, dB + 128 * k, 1);
          mbar_wait(barF, fph & 1);
          fph ^= 5u;
#pragma unroll
          for (int k = 0; k < 4; k++) wgmma_ss_n224(acc, dA + 1024 + 2 * k, dC + 128 * k, 1);
          wg_commit();
          asm volatile("bar.arrive %0, 256;" :: "r"(otT) : "memory");
          wg_wait0();
          if (el) { mbar_arrive(barE + 16); mbar_arrive(barE); }
        }
        fence_regs(acc);
#pragma unroll
        for (int i = 0; i < 16; i++) {
          h[16 + i] = mul2(h[16 + i], pack(acc[2 * i], acc[2 * i + 1]));
          h[32 + i] = mul2(pack_relu(acc[64 + 2 * i], acc[64 + 2 * i + 1]), pack(acc[32 + 2 * i], acc[32 + 2 * i + 1]));
        }
#pragma unroll
        for (int i = 0; i < 8; i++) h[48 + i] = mul2(h[48 + i], pack(acc[96 + 2 * i], acc[96 + 2 * i + 1]));
      }
      if (el) mbar_arrive_remote(peerR);
      uint32_t hold[16];
      float a[64];
      def_regs(hold);
      auto issue = [&](int c) {
        const uint64_t d0 = mkdesc(s0 + (c == 1 ? SM_ST + STAGE : c == 3 ? 32768 : 0), c < 2 ? 32768 : SM_ST, 1024);
        mbar_wait(barW + 8 * c, layer);
        asm volatile("bar.sync %0, 256;" :: "r"(myT) : "memory");
        wg_fence();
#pragma unroll
        for (int t = 0; t < 14; t++) wgmma_rs_n128(a, h[4 * t], h[4 * t + 1], h[4 * t + 2], h[4 * t + 3], d0 + 128 * t, t > 0);
        wg_commit();
        asm volatile("bar.arrive %0, 256;" :: "r"(otT) : "memory");
      };
      auto keep = [&](int c, bool direct) {
        mbar_wait(inB0 + 8 * c, layer);
        uint4 o[4];
        const uint32_t ib = inA0 + c * 2048, voff = voff0 ^ ((c & 1) << 6);
#pragma unroll
        for (int v = 0; v < 4; v++) o[v] = lds(ib + (voff ^ ((v & 1) << 6)) + (v >> 1) * 1024);
#pragma unroll
        for (int v = 0; v < 4; v++) {
          const uint32_t x = (add2(o[v].x, hold[4 * v]) & ~1u) | tag, y = add2(o[v].y, hold[4 * v + 1]), z = add2(o[v].z, hold[4 * v + 2]), w = add2(o[v].w, hold[4 * v + 3]);
          const uint32_t off = (voff ^ ((v & 1) << 6)) + (v >> 1) * 1024;
          if (!direct || warp == jf) sts(ib + off, x, y, z, w);
          else st_relaxed((uint4*)(gdst + c * 16384 + off), x, y, z, w);
        }
      };
      auto bulk_out = [&](int c) {
        asm volatile("fence.proxy.async.shared::cta;" ::: "memory");
        __syncwarp();
        if (lane == 0 && warp != jf) asm volatile("cp.async.bulk.global.shared::cta.bulk_group [%0], [%1], 2048;" :: "l"(gdst + c * 16384), "r"(inA0 + c * 2048) : "memory");
      };
#pragma unroll 1
      for (int c = 0; c < 4; c++) {
        issue(c);
        if (c > 0) {
          keep(c - 1, c == 3);
          if (c < 3) bulk_out(c - 1);
          if (c < 3 && warp == jf && lane == 0) mbar_arrive(barN - 8 + 8 * c);
        } else {
#pragma unroll
          for (int o = 16; o > 0; o >>= 1) { vs[0] += __shfl_xor_sync(0xffffffffu, vs[0], o); vs[1] += __shfl_xor_sync(0xffffffffu, vs[1], o); }
#pragma unroll
          for (int r = 0; r < 2; r++) { const float f = __fdividef(1.f, fmaf(vs[r], 1.f / 512.f, 1e-5f)); vs[r] = __uint_as_float(pack(f, f)); }
          mbar_wait(barR, layer);
        }
        const uint32_t voff = voff0 ^ ((c & 1) << 6) ^ 32;
        wg_wait0();
        if (el) mbar_arrive(barX + 8 * c);
        fence_regs(a);
#pragma unroll
        for (int v = 0; v < 4; v++) {
          const int b = 32 + (v & 1) * 4 + (v >> 1) * 2;
          asm volatile("st.async.shared::cluster.mbarrier::complete_tx::bytes.v4.u32 [%0], {%1,%2,%3,%4}, [%5];"
                       :: "r"(outA + c * 2048 + (voff ^ ((v & 1) << 6)) + (v >> 1) * 1024), "r"(pack(a[b], a[b + 1])), "r"(pack(a[b + 8], a[b + 9])),
                          "r"(pack(a[b + 16], a[b + 17])), "r"(pack(a[b + 24], a[b + 25])), "r"(outB + 8 * c) : "memory");
        }
#pragma unroll
        for (int v = 0; v < 4; v++)
#pragma unroll
          for (int m = 0; m < 4; m++) { const int b = (v & 1) * 4 + (v >> 1) * 2 + 8 * m; hold[4 * v + m] = pack(a[b], a[b + 1]); }
      }
      const uint32_t isloc = (q & 1) == odd;
      const uint32_t ps0 = (warp * 16 + (g ^ (2 * q))) * 16, ps1 = (ps0 ^ 64) + 128;
      auto done3 = [&]() {
        __syncwarp();
        if (lane == 0) {
          if (warp == jf) { asm volatile("st.shared.u32 [%0], %1;" :: "r"(barC), "r"(clk()) : "memory"); mbar_arrive(barO); }
          mbar_arrive_remote(peerR + 8);
          asm volatile("cp.async.bulk.commit_group;" ::: "memory");
        }
      };
      {
        mbar_wait2(inB0 + 24, layer, barZ, layer);
        uint4 o[4];
        const uint32_t voff = voff0 ^ 64;
#pragma unroll
        for (int v = 0; v < 4; v++) o[v] = lds(inA0 + 6144 + (voff ^ ((v & 1) << 6)) + (v >> 1) * 1024);
        char* xd = (char*)(P.X + ((jf * 16 + g) * 128 + rb * 8 + warp) * 8);
#pragma unroll
        for (int v = 0; v < 4; v++)
          st_relaxed((uint4*)(xd + ((voff ^ ((v & 1) << 6)) & 127) + (v >> 1) * 131072), add2(o[v].x, hold[4 * v]) & ~TM, add2(o[v].y, hold[4 * v + 1]),
                     add2(o[v].z, hold[4 * v + 2]), add2(o[v].w, hold[4 * v + 3]));
        done3();
      }
      {
        uint4 rv[8], u[2];
        const uint32_t s2[2] = {__float_as_uint(vs[0]), __float_as_uint(vs[1])};
        const uint32_t late = q >> 1, rtag = late ? TAG_P : tag, rtm = late ? TM : 1, skip = isloc && !late;
        const char* g0 = late ? (const char*)(P.X + (((q & 1) * 16 + 2 * warp) * 128 + cta) * 8) + (ps0 & 127) : (const char*)(P.Pp + cta * 4096 + 2048 + q * 128) + ps0;
        const char* g1 = late ? (const char*)(P.X + (((q & 1) * 16 + 2 * warp + 1) * 128 + cta) * 8) + (ps1 & 127) : (const char*)(P.Pp + cta * 4096 + 2048 + q * 128) + ps1;
        const uint32_t gs = late ? 32 * 16384 : 4096;
        const uint4* ga[8];
#pragma unroll
        for (int i = 0; i < 8; i++) { ga[i] = (const uint4*)(((i >> 2) ? g1 : g0) + ((pr ^ i) & 3) * gs); rv[i] = make_uint4(tag, 0, 0, 0); asm volatile("" : "+l"(ga[i])); }
        {
          const uint32_t tb = s0 + SM_RF + lane * 16;
          mbar_wait(barU + 8, layer);
#pragma unroll
          for (int k = 0; k < 4; k++) { f1[k] = lds(tb + k * 512); twa[k] = lds(tb + (4 + k) * 512); f2[k] = lds(tb + (10 + k) * 512); }
          twb[0] = lds(tb + 8 * 512); twb[1] = lds(tb + 9 * 512);
        }
        mbar_wait(barO, layer);
        asm volatile("ld.shared.u32 %0, [%1];" : "=r"(t0) : "r"(barC) : "memory");
        wait_until(t0, T_LAST);
#pragma unroll
        for (int i = 0; i < 8; i++) ld_pred(rv[i], ga[i], !(skip && (i & 3) == 0));
        const uint32_t ub = s0 + (pr ^ 1) * 4096 + (q & 1) * 2048;
        mbar_wait(barU, layer);
        u[0] = lds(ub + (q < 2) * SM_P0 + ps0); u[1] = lds(ub + (q < 2) * SM_P0 + ps1);
        sx[0] = sx[1] = sq[0] = sq[1] = 0.f;
#pragma unroll
        for (int r = 0; r < 2; r++) {
          xr[r][0] = make_uint4(fma2(u[r].x, s2[r], xr[r][0].x), fma2(u[r].y, s2[r], xr[r][0].y), fma2(u[r].z, s2[r], xr[r][0].z), fma2(u[r].w, s2[r], xr[r][0].w));
          acc_stats(xr[r][0], sx[r], sq[r]);
        }
        const uint32_t u1 = s0 + SM_IN + jf * 8192 + 4096;
        u[0] = u[1] = make_uint4(0, 0, 0, 0);
        lds_pred(u[0], u1 + ps0, skip); lds_pred(u[1], u1 + ps1, skip);
        repoll<5>(rv, rtag, rtm, [&](int i) { return ga[i]; });
#pragma unroll
        for (int r = 0; r < 2; r++) {
          const uint4 t = add2v(add2v(add2v(rv[4 * r], rv[4 * r + 1]), add2v(rv[4 * r + 2], rv[4 * r + 3])), u[r]);
          xr[r][1] = make_uint4(fma2(t.x, s2[r], xr[r][1].x), fma2(t.y, s2[r], xr[r][1].y), fma2(t.z, s2[r], xr[r][1].z), fma2(t.w, s2[r], xr[r][1].w));
        }
        __syncwarp();
      }
      if (lane == 0) { asm volatile("cp.async.bulk.wait_group.read 0;" ::: "memory"); mbar_arrive(barQ); }
    }
    {
      PHASE_IDS
      uint32_t* op = P.out + (size_t)(cta + 256 * warp) * 256 + q * 32 + g;
#pragma unroll
      for (int r = 0; r < 2; r++)
#pragma unroll
        for (int st = 0; st < 2; st++) {
          uint32_t* p = op + r * (128 * 256) + st * 128;
          p[0] = xr[r][st].x; p[8] = xr[r][st].y; p[16] = xr[r][st].z; p[24] = xr[r][st].w;
        }
    }
    mbar_wait(barD, 1);
  }
}

typedef CUresult (*EncFn)(CUtensorMap*, CUtensorMapDataType, cuuint32_t, void*, const cuuint64_t*, const cuuint64_t*, const cuuint32_t*,
                          const cuuint32_t*, CUtensorMapInterleave, CUtensorMapSwizzle, CUtensorMapL2promotion, CUtensorMapFloatOOBfill);
static void mk(EncFn enc, CUtensorMap* tm, const void* base, int rank, const cuuint64_t* gd, const cuuint64_t* gs, const cuuint32_t* bd, bool swz = true) {
  const cuuint32_t es[5] = {1, 1, 1, 1, 1};
  enc(tm, CU_TENSOR_MAP_DATA_TYPE_BFLOAT16, rank, (void*)base, gd, gs, bd, es, CU_TENSOR_MAP_INTERLEAVE_NONE,
      swz ? CU_TENSOR_MAP_SWIZZLE_128B : CU_TENSOR_MAP_SWIZZLE_NONE, swz ? CU_TENSOR_MAP_L2_PROMOTION_L2_128B : CU_TENSOR_MAP_L2_PROMOTION_NONE, CU_TENSOR_MAP_FLOAT_OOB_FILL_NONE);
}

extern "C" void kernel_launch(void* const* d_in, const int* in_sizes, int n_in, void* d_out, int out_size) {
  static EncFn enc = nullptr;
  static void *abuf = nullptr, *pbuf = nullptr, *tbuf = nullptr;
  if (!enc) {
    void* fn = nullptr;
    cudaDriverEntryPointQueryResult qr;
    cudaGetDriverEntryPoint("cuTensorMapEncodeTiled", &fn, cudaEnableDefault, &qr);
    enc = (EncFn)fn;
    cudaGetSymbolAddress(&abuf, g_X); cudaGetSymbolAddress(&pbuf, g_P); cudaGetSymbolAddress(&tbuf, g_tab);
    cudaFuncSetAttribute(fused_kernel, cudaFuncAttributeMaxDynamicSharedMemorySize, SM_TOTAL);
  }
  Params P;
  const void *wg = d_in[4], *wu = d_in[5], *wdn = d_in[6];
  {
    const cuuint64_t gd[4] = {64, 16, 128, 8}, gs[3] = {131072, 128, 16384};
    const cuuint32_t bd[4] = {64, 16, 8, 1};
    mk(enc, &P.a, abuf, 4, gd, gs, bd);
    const cuuint64_t wd_[3] = {4112, 8, 16}, ws[2] = {256 * 514, 16 * 514};
    const cuuint32_t wb[3] = {40, 8, 16};
    mk(enc, &P.wr, d_in[1], 3, wd_, ws, wb, false); mk(enc, &P.wi, d_in[2], 3, wd_, ws, wb, false);
  }
  {
    const cuuint64_t gd[5] = {64, 2, 32, 8, 28}, gs[4] = {3584, 16 * 3584, 2 * 3584, 128};
    const cuuint32_t b2[5] = {64, 2, 4, 8, 2}, b1[5] = {64, 2, 4, 8, 1};
    mk(enc, &P.g2, wg, 5, gd, gs, b2); mk(enc, &P.g1, wg, 5, gd, gs, b1);
    mk(enc, &P.u2, wu, 5, gd, gs, b2); mk(enc, &P.u1, wu, 5, gd, gs, b1);
    const cuuint64_t hd[4] = {1792, 2, 32, 8};
    const cuuint32_t hb[4] = {32, 2, 4, 8};
    mk(enc, &P.gh, wg, 4, hd, gs, hb); mk(enc, &P.uh, wu, 4, hd, gs, hb);
  }
  {
    const cuuint64_t gd[2] = {512, 1792}, gs[1] = {1024};
    const cuuint32_t b192[2] = {64, 192}, b32[2] = {64, 32};
    mk(enc, &P.w192, wdn, 2, gd, gs, b192); mk(enc, &P.w32, wdn, 2, gd, gs, b32);
  }
  P.x = (const uint32_t*)d_in[0]; P.tab = (const uint4*)tbuf; P.X = (uint4*)abuf; P.Pp = (uint4*)pbuf;
  P.out = (uint32_t*)d_out; P.wg = (const char*)wg; P.wu = (const char*)wu; P.wdn = (const char*)wdn;

  fused_kernel<<<128, 384, SM_TOTAL>>>(P);
}
```
